```python
import torch

def _softmax(x, axis=-1):
    return torch.softmax(x, dim=axis)
def _gelu(x):
    return torch.nn.functional.gelu(x, approximate="tanh")
def _silu(x):
    return torch.nn.functional.silu(x)
def _sigmoid(x):
    return torch.sigmoid(x)
def _layernorm(x, axis=-1, eps=1e-5):
    m = x.mean(dim=axis, keepdim=True)
    v = x.var(dim=axis, keepdim=True, unbiased=False)
    return (x - m) / torch.sqrt(v + eps)
def _scatter_add(tgt, idx, src, axis=0):
    return tgt.clone().index_add_(axis, idx, src)
def _segment_sum(src, seg, n):
    out = torch.zeros((n,) + src.shape[1:], dtype=src.dtype)
    return out.index_add_(0, seg, src)
def _pad(x, pw):
    flat = tuple(v for pair in reversed(pw) for v in pair)
    return torch.nn.functional.pad(x, flat)

kernel_name = 'gated_mix__ssm_conv_s4__mixer_channel_mlp__prompt'

def setup_inputs():

    _w = (lambda a: (lambda t: t.to(torch.bfloat16) if t.is_floating_point() else t)(torch.as_tensor(a)))
    def _A_setup():
        B, L, D, N = 1, 2048, 576, 128
        A_re = -(lambda _x: torch.exp(torch.as_tensor(_x)))((lambda *s: torch.randn(*s, dtype=torch.bfloat16) * 3.2)(D, N))
        A_im = torch.pi * (lambda *s: torch.randn(*s, dtype=torch.bfloat16) * 0.1)(D, N)
        B_re = (lambda *s: torch.randn(*s, dtype=torch.bfloat16) * 0.2)(D, N)
        B_im = (lambda *s: torch.randn(*s, dtype=torch.bfloat16) * 0.2)(D, N)
        C_re = (lambda *s: torch.randn(*s, dtype=torch.bfloat16) * 0.2)(D, N)
        C_im = (lambda *s: torch.randn(*s, dtype=torch.bfloat16) * 0.2)(D, N)
        log_dt = (lambda *s: torch.randn(*s, dtype=torch.bfloat16) * 0.1)(D) * 0.5 - 4.0
        Dskip = (lambda *s: torch.randn(*s, dtype=torch.bfloat16) * 0.1)(D)
        return {
            "u": _w((lambda *s: torch.randn(*s, dtype=torch.bfloat16) * 0.05)(B, L, D)),
            "A_re": _w(A_re),
            "A_im": _w(A_im),
            "B_re": _w(B_re),
            "B_im": _w(B_im),
            "C_re": _w(C_re),
            "C_im": _w(C_im),
            "log_dt": _w(log_dt),
            "Dskip": _w(Dskip),
        }
    _A_in = _A_setup()

    def _B_setup():
        B, S, D, F = 1, 2048, 576, 4608
        return {
            "x": _w((lambda *s: torch.randn(*s, dtype=torch.bfloat16) * 0.05)(B, S, D)),
            "w1": _w((lambda *s: torch.randn(*s, dtype=torch.bfloat16) * 0.8)(D, F) * (D ** -0.5)),
            "b1": _w((lambda *s: torch.randn(*s, dtype=torch.bfloat16) * 0.4)(F)),
            "w2": _w((lambda *s: torch.randn(*s, dtype=torch.bfloat16) * 0.05)(F, D) * (F ** -0.5)),
            "b2": _w((lambda *s: torch.randn(*s, dtype=torch.bfloat16) * 0.05)(D)),
        }
    _B_in = _B_setup()

    return {
        "A_u": _A_in["u"],
        "A_A_re": _A_in["A_re"],
        "A_A_im": _A_in["A_im"],
        "A_B_re": _A_in["B_re"],
        "A_B_im": _A_in["B_im"],
        "A_C_re": _A_in["C_re"],
        "A_C_im": _A_in["C_im"],
        "A_log_dt": _A_in["log_dt"],
        "A_Dskip": _A_in["Dskip"],
        "B_x": _B_in["x"],
        "B_w1": _B_in["w1"],
        "B_b1": _B_in["b1"],
        "B_w2": _B_in["w2"],
        "B_b2": _B_in["b2"],
        "gate_w": _w((lambda *s: torch.randn(*s, dtype=torch.bfloat16) * 0.05)(576) * 16.0),
    }

def reference(A_u, A_A_re, A_A_im, A_B_re, A_B_im, A_C_re, A_C_im, A_log_dt, A_Dskip, B_x, B_w1, B_b1, B_w2, B_b2, gate_w):
    def _A_ref(u, A_re, A_im, B_re, B_im, C_re, C_im, log_dt, Dskip):
        Bsz, L, D = u.shape
        dt = torch.exp(log_dt)[:, None]
        A = A_re + 1j * A_im
        Bc = B_re + 1j * B_im
        Cc = C_re + 1j * C_im
        logdA = dt * A
        dB = dt * Bc
        l = (lambda x, dt: x.to(dt))(torch.arange(L), A_re.dtype)
        P = torch.exp(logdA[:, :, None] * l[None, None, :])
        K = torch.einsum("dn,dnl,dn->dl", Cc, P, dB).real
        L2 = 2 * L
        Kp = _pad(K, ((0, 0), (0, L)))
        up = (lambda x, *d: x.permute(*d))(u, 0, 2, 1)
        up = _pad(up, ((0, 0), (0, 0), (0, L)))
        Kf = (lambda x, axes=(-2,-1): torch.fft.rfft2(x.float(), dim=axes))(Kp[:, None, :], axes=(-2, -1))
        Uf = (lambda x, axes=(-2,-1): torch.fft.rfft2(x.float(), dim=axes))(up[:, :, None, :], axes=(-2, -1))
        Yf = Uf * Kf[None, :, :, :]
        y = (lambda x, s, axes=(-2,-1): torch.fft.irfft2(x, s=s, dim=axes).to(torch.bfloat16))(Yf, (1, L2), axes=(-2, -1))[:, :, 0, :L]
        y = (lambda x, *d: x.permute(*d))(y, 0, 2, 1) + u * Dskip[None, None, :]
        return y

    def _B_ref(x, w1, b1, w2, b2):
        y = _layernorm(x, axis=-1)
        h = _gelu(torch.einsum("bsd,df->bsf", y, w1) + b1)
        return torch.einsum("bsf,fd->bsd", h, w2) + b2

    x = A_u
    g = _sigmoid((x * gate_w).sum(-1, keepdims=True))
    a = _A_ref(x, A_A_re, A_A_im, A_B_re, A_B_im, A_C_re, A_C_im, A_log_dt, A_Dskip)
    b = _B_ref(x, B_w1, B_b1, B_w2, B_b2)
    return g * a + (1 - g) * b
```

```cpp
#include <cuda_runtime.h>
#include <cuda_bf16.h>
#include <cuda.h>
#include <stdint.h>

namespace {

constexpr int L_SEQ = 2048;
constexpr int D_MODEL = 576;
constexpr int F_DIM = 4608;
constexpr int N_MODES = 128;

typedef __nv_bfloat16 bf16;

__device__ uint2 g_rowstat[L_SEQ];
__device__ float g_gate[L_SEQ];
__device__ bf16 g_aT[D_MODEL * L_SEQ];
__device__ uint4 g_part[16 * 9 * 8 * 8 * 4 * 32];
__device__ unsigned g_epoch;

#define DBG(slot)
#define DBG1(slot)

__device__ __forceinline__ uint32_t smem_u32(const void* p) { return (uint32_t)__cvta_generic_to_shared(p); }
__device__ __forceinline__ float bf16r(float x) { return __bfloat162float(__float2bfloat16_rn(x)); }
__device__ __forceinline__ uint32_t pack_bf16(float lo, float hi) {
    uint32_t r;
    asm("cvt.rn.bf16x2.f32 %0, %1, %2;" : "=r"(r) : "f"(hi), "f"(lo));
    return r;
}
__device__ __forceinline__ float bf_lo(uint32_t v) { return __uint_as_float(v << 16); }
__device__ __forceinline__ float bf_hi(uint32_t v) { return __uint_as_float(v & 0xffff0000u); }

__device__ __forceinline__ void mbar_init(uint32_t bar, int cnt) {
    asm volatile("mbarrier.init.shared::cta.b64 [%0], %1;" ::"r"(bar), "r"(cnt));
}
__device__ __forceinline__ void mbar_expect(uint32_t bar, int bytes) {
    asm volatile("mbarrier.arrive.expect_tx.shared::cta.b64 _, [%0], %1;" ::"r"(bar), "r"(bytes) : "memory");
}
__device__ __forceinline__ void mbar_arrive_cluster(uint32_t bar, uint32_t cta) {
    asm volatile(
        "{\n.reg .b32 ra;\nmapa.shared::cluster.u32 ra, %0, %1;\n"
        "mbarrier.arrive.shared::cluster.b64 _, [ra];\n}\n" ::"r"(bar), "r"(cta) : "memory");
}
__device__ __forceinline__ bool mbar_try(uint32_t bar, int parity) {
    uint32_t ok;
    asm volatile(
        "{\n.reg .pred p;\nmbarrier.try_wait.parity.shared::cta.b64 p, [%1], %2;\nselp.u32 %0, 1, 0, p;\n}\n"
        : "=r"(ok) : "r"(bar), "r"(parity) : "memory");
    return ok != 0;
}
__device__ __forceinline__ void mbar_wait(uint32_t bar, int parity) {
    asm volatile(
        "{\n.reg .pred p;\n.reg .u32 n;\nmov.u32 n, 0;\n"
        "WAIT_LOOP:\n"
        "mbarrier.try_wait.parity.shared::cta.b64 p, [%0], %1;\n"
        "@p bra WAIT_DONE;\n"
        "add.u32 n, n, 1;\n"
        "setp.lt.u32 p, n, 4194304;\n"
        "@p bra WAIT_LOOP;\n"
        "trap;\n"
        "WAIT_DONE:\n}\n" ::"r"(bar), "r"(parity) : "memory");
}
__device__ __forceinline__ void tma2d(uint32_t dst, const CUtensorMap* m, int c0, int c1, uint32_t bar) {
    asm volatile(
        "cp.async.bulk.tensor.2d.shared::cluster.global.mbarrier::complete_tx::bytes [%0], [%1, {%3,%4}], [%2];"
        ::"r"(dst), "l"(m), "r"(bar), "r"(c0), "r"(c1) : "memory");
}
__device__ __forceinline__ void tma2d_mc(uint32_t dst, const CUtensorMap* m, int c0, int c1, uint32_t bar,
                                         uint16_t mask) {
    asm volatile(
        "cp.async.bulk.tensor.2d.shared::cluster.global.mbarrier::complete_tx::bytes.multicast::cluster "
        "[%0], [%1, {%3,%4}], [%2], %5;"
        ::"r"(dst), "l"(m), "r"(bar), "r"(c0), "r"(c1), "h"(mask) : "memory");
}
__device__ __forceinline__ void ldsm_x4(uint32_t (&r)[4], uint32_t addr) {
    asm volatile("ldmatrix.sync.aligned.m8n8.x4.shared.b16 {%0,%1,%2,%3}, [%4];"
                 : "=r"(r[0]), "=r"(r[1]), "=r"(r[2]), "=r"(r[3]) : "r"(addr) : "memory");
}
#define WG_FENCE() asm volatile("wgmma.fence.sync.aligned;\n" ::: "memory")
#define WG_COMMIT() asm volatile("wgmma.commit_group.sync.aligned;\n" ::: "memory")
#define WG_WAIT(n) asm volatile("wgmma.wait_group.sync.aligned %0;\n" ::"n"(n) : "memory")

template <int SCALE_D, int OFF>
__device__ __forceinline__ void wgmma_rs_n64(float (&d)[32], const uint32_t (&a)[4], uint32_t desc_lo) {
    asm volatile(
        "{\n.reg .pred p;\n.reg .b32 lo;\n.reg .b64 dsc;\nsetp.ne.b32 p, %37, 0;\n"
        "add.u32 lo, %36, %38;\nmov.b64 dsc, {lo, 0x40000040};\n"
        "wgmma.mma_async.sync.aligned.m64n64k16.f32.bf16.bf16 "
        "{%0,%1,%2,%3,%4,%5,%6,%7,%8,%9,%10,%11,%12,%13,%14,%15,%16,%17,%18,%19,%20,%21,%22,%23,%24,%25,%26,%27,%28,%29,%30,%31},"
        "{%32,%33,%34,%35}, dsc, p, 1, 1, 1;\n}\n"
        : "+f"(d[0]), "+f"(d[1]), "+f"(d[2]), "+f"(d[3]), "+f"(d[4]), "+f"(d[5]), "+f"(d[6]), "+f"(d[7]),
          "+f"(d[8]), "+f"(d[9]), "+f"(d[10]), "+f"(d[11]), "+f"(d[12]), "+f"(d[13]), "+f"(d[14]), "+f"(d[15]),
          "+f"(d[16]), "+f"(d[17]), "+f"(d[18]), "+f"(d[19]), "+f"(d[20]), "+f"(d[21]), "+f"(d[22]), "+f"(d[23]),
          "+f"(d[24]), "+f"(d[25]), "+f"(d[26]), "+f"(d[27]), "+f"(d[28]), "+f"(d[29]), "+f"(d[30]), "+f"(d[31])
        : "r"(a[0]), "r"(a[1]), "r"(a[2]), "r"(a[3]), "r"(desc_lo), "n"(SCALE_D), "n"(OFF));
}
template <int OFF, int AOFF>
__device__ __forceinline__ void wgmma_ss_n64(float (&d)[32], uint32_t adesc_lo, uint32_t desc_lo) {
    asm volatile(
        "{\n.reg .pred p;\n.reg .b32 lo;\n.reg .b64 dsc, dsa;\nsetp.ne.b32 p, 1, 0;\n"
        "add.u32 lo, %33, %34;\nmov.b64 dsc, {lo, 0x40000040};\n"
        "add.u32 lo, %32, %35;\nmov.b64 dsa, {lo, 0x40000040};\n"
        "wgmma.mma_async.sync.aligned.m64n64k16.f32.bf16.bf16 "
        "{%0,%1,%2,%3,%4,%5,%6,%7,%8,%9,%10,%11,%12,%13,%14,%15,%16,%17,%18,%19,%20,%21,%22,%23,%24,%25,%26,%27,%28,%29,%30,%31},"
        "dsa, dsc, p, 1, 1, 0, 1;\n}\n"
        : "+f"(d[0]), "+f"(d[1]), "+f"(d[2]), "+f"(d[3]), "+f"(d[4]), "+f"(d[5]), "+f"(d[6]), "+f"(d[7]),
          "+f"(d[8]), "+f"(d[9]), "+f"(d[10]), "+f"(d[11]), "+f"(d[12]), "+f"(d[13]), "+f"(d[14]), "+f"(d[15]),
          "+f"(d[16]), "+f"(d[17]), "+f"(d[18]), "+f"(d[19]), "+f"(d[20]), "+f"(d[21]), "+f"(d[22]), "+f"(d[23]),
          "+f"(d[24]), "+f"(d[25]), "+f"(d[26]), "+f"(d[27]), "+f"(d[28]), "+f"(d[29]), "+f"(d[30]), "+f"(d[31])
        : "r"(adesc_lo), "r"(desc_lo), "n"(OFF), "n"(AOFF));
}
constexpr int NAF = 34;
template <int S, int FIRST>
__device__ __forceinline__ void mma_stage(float (&d)[32], const uint32_t (&af)[NAF][4], uint32_t desc_lo,
                                          uint32_t adesc_lo) {
    constexpr int B = (S * 96 * 128) >> 4;
    wgmma_rs_n64<FIRST ? 0 : 1, B + 0 * 128>(d, af[S * 6 + 0], desc_lo);
    wgmma_rs_n64<1, B + 1 * 128>(d, af[S * 6 + 1], desc_lo);
    wgmma_rs_n64<1, B + 2 * 128>(d, af[S * 6 + 2], desc_lo);
    wgmma_rs_n64<1, B + 3 * 128>(d, af[S * 6 + 3], desc_lo);
    if constexpr (S < 5) {
        wgmma_rs_n64<1, B + 4 * 128>(d, af[S * 6 + 4], desc_lo);
        wgmma_rs_n64<1, B + 5 * 128>(d, af[S * 6 + 5], desc_lo);
    } else {
        wgmma_ss_n64<B + 4 * 128, 4>(d, adesc_lo, desc_lo);
        wgmma_ss_n64<B + 5 * 128, 6>(d, adesc_lo, desc_lo);
    }
}
__device__ __forceinline__ void mma_stage_rt(int s, float (&d)[32], const uint32_t (&af)[NAF][4], uint32_t desc_lo,
                                             uint32_t adesc_lo) {
    if (s == 0) mma_stage<0, 1>(d, af, desc_lo, adesc_lo);
    if (s == 1) mma_stage<1, 0>(d, af, desc_lo, adesc_lo);
    if (s == 2) mma_stage<2, 0>(d, af, desc_lo, adesc_lo);
    if (s == 3) mma_stage<3, 0>(d, af, desc_lo, adesc_lo);
    if (s == 4) mma_stage<4, 0>(d, af, desc_lo, adesc_lo);
    if (s == 5) mma_stage<5, 0>(d, af, desc_lo, adesc_lo);
}
__device__ __forceinline__ void stsm_x4(const uint32_t (&r)[4], uint32_t addr) {
    asm volatile("stmatrix.sync.aligned.m8n8.x4.shared.b16 [%4], {%0,%1,%2,%3};"
                 ::"r"(r[0]), "r"(r[1]), "r"(r[2]), "r"(r[3]), "r"(addr) : "memory");
}
__device__ __forceinline__ void fence_acc(float (&d)[32]) {
#pragma unroll
    for (int i = 0; i < 32; i++) asm volatile("" : "+f"(d[i])::"memory");
}

__device__ __forceinline__ float gelu_tanh(float x) {
    const float k0 = 0.7978845608028654f, k1 = 0.7978845608028654f * 0.044715f;
    float u = x * fmaf(x * x, k1, k0);
    float th;
    asm("tanh.approx.f32 %0, %1;" : "=f"(th) : "f"(u));
    float hx = 0.5f * x;
    return fmaf(hx, th, hx);
}

__device__ __forceinline__ uint32_t hadd2_bf(uint32_t a, uint32_t b) {
    uint32_t r;
    asm("add.rn.bf16x2 %0, %1, %2;" : "=r"(r) : "r"(a), "r"(b));
    return r;
}
__device__ __forceinline__ uint32_t hsub2_bf(uint32_t a, uint32_t b) {
    uint32_t r;
    asm("sub.rn.bf16x2 %0, %1, %2;" : "=r"(r) : "r"(a), "r"(b));
    return r;
}
__device__ __forceinline__ uint32_t hmul2_bf(uint32_t a, uint32_t b) {
    uint32_t r;
    asm("mul.rn.bf16x2 %0, %1, %2;" : "=r"(r) : "r"(a), "r"(b));
    return r;
}
__device__ __forceinline__ uint32_t hfma2_bf(uint32_t a, uint32_t b, uint32_t c) {
    uint32_t r;
    asm("fma.rn.bf16x2 %0, %1, %2, %3;" : "=r"(r) : "r"(a), "r"(b), "r"(c));
    return r;
}
namespace ssm {
constexpr int O_H = 0;
constexpr int O_L = 12288;
constexpr int HL_END = O_L + 16384;
constexpr int O_Q = 0;
constexpr int O_Q12 = 5120;
constexpr int O_Q34 = O_Q12 + 1280;
constexpr int O_Y12 = O_Q34 + 2048 - 2176;
constexpr int O_Y34 = O_Y12 + 8704 - 4352;
constexpr int O_W3 = O_Y34 + 8704 + 256;
constexpr int O_W4 = O_W3 + 2048 + 256;
constexpr int O_W5 = O_W4 + 2048;
constexpr int O_U = HL_END;
constexpr int O_RAW = O_U + 6144;
constexpr int O_W1 = O_U + 6144 + 256;
constexpr int O_W2 = O_W1 + 3072 + 256;
constexpr int O_ST = O_RAW;
constexpr int O_KN = O_W2 + 3072;
constexpr int O_A12 = O_KN + 1344;
constexpr int O_A3 = O_A12 + 384;
constexpr int O_KQ = O_A3 + 304;
constexpr int WG_BYTES = 44032;
static_assert(O_W5 + 2048 <= HL_END && O_KQ + 16 <= WG_BYTES && WG_BYTES % 1024 == 0 && O_RAW + 8192 <= WG_BYTES, "map");

struct cplx { float r, i; };
__device__ __forceinline__ cplx cmul(cplx a, cplx b) {
    cplx o;
    o.r = fmaf(a.r, b.r, -a.i * b.i);
    o.i = fmaf(a.r, b.i, a.i * b.r);
    return o;
}
__device__ __forceinline__ cplx cexp_l(float lr, float li, float l) {
    const float e = exp2f((lr * l) * 1.4426950408889634f);
    const float ang = li * l;
    const float k = rintf(ang * 0.15915494309189535f);
    float r = fmaf(k, -6.2831854820251465f, ang);
    r = fmaf(k, 1.7484556000744487e-07f, r);
    cplx o;
    o.r = e * __cosf(r);
    o.i = e * __sinf(r);
    return o;
}
template <typename T> __device__ __forceinline__ T* sp(uint32_t a) {
    return reinterpret_cast<T*>(__cvta_shared_to_generic(a));
}
__device__ __forceinline__ void sts32(uint32_t a, uint32_t v) { *sp<uint32_t>(a) = v; }
__device__ __forceinline__ void sts16(uint32_t a, uint32_t v) { *sp<unsigned short>(a) = (unsigned short)v; }
__device__ __forceinline__ uint32_t lds16(uint32_t a) { return *sp<unsigned short>(a); }
__device__ __forceinline__ uint32_t lds32(uint32_t a) { return *sp<uint32_t>(a); }
__device__ __forceinline__ float ldsf(uint32_t a) { return *sp<float>(a); }
__device__ __forceinline__ uint2 lds64(uint32_t a) { return *sp<uint2>(a); }
__device__ __forceinline__ void sts64(uint32_t a, uint32_t x, uint32_t y) { *sp<uint2>(a) = make_uint2(x, y); }
__device__ __forceinline__ void sts64f(uint32_t a, float x, float y) { *sp<float2>(a) = make_float2(x, y); }
__device__ __forceinline__ void sts128(uint32_t a, uint32_t x, uint32_t y, uint32_t z, uint32_t w) {
    *sp<uint4>(a) = make_uint4(x, y, z, w);
}
__device__ __forceinline__ uint4 lds128(uint32_t a) { return *sp<uint4>(a); }
__device__ __forceinline__ void wg_bar(int id) { asm volatile("bar.sync %0, 128;" ::"r"(id) : "memory"); }
__device__ __forceinline__ uint32_t u_addr(uint32_t sb, int grp) {
    const int gq = grp + 128;
    return sb + O_U + (gq >> 3) * 128 + (((gq ^ (gq >> 3)) & 7) << 4);
}
template <int SCALE_D, int OA, int OB>
__device__ __forceinline__ void wgmma_ss_n32(float (&d)[16], uint32_t dl) {
    asm volatile(
        "{\n.reg .pred p;\n.reg .b32 lo;\n.reg .b64 x, y;\nsetp.ne.b32 p, %17, 0;\n"
        "add.u32 lo, %16, %18;\nmov.b64 x, {lo, 0x40000040};\nadd.u32 lo, %16, %19;\nmov.b64 y, {lo, 0x40000040};\n"
        "wgmma.mma_async.sync.aligned.m64n32k16.f32.bf16.bf16 "
        "{%0,%1,%2,%3,%4,%5,%6,%7,%8,%9,%10,%11,%12,%13,%14,%15}, x, y, p, 1, 1, 0, 0;\n}\n"
        : "+f"(d[0]), "+f"(d[1]), "+f"(d[2]), "+f"(d[3]), "+f"(d[4]), "+f"(d[5]), "+f"(d[6]), "+f"(d[7]),
          "+f"(d[8]), "+f"(d[9]), "+f"(d[10]), "+f"(d[11]), "+f"(d[12]), "+f"(d[13]), "+f"(d[14]), "+f"(d[15])
        : "r"(dl), "n"(SCALE_D), "n"(OA), "n"(OB));
}
template <int OB>
__device__ __forceinline__ void wgmma_rs_n32(float (&d)[16], uint32_t a0, uint32_t a1, uint32_t a2, uint32_t a3,
                                             uint32_t dl) {
    asm volatile(
        "{\n.reg .pred p;\n.reg .b32 lo;\n.reg .b64 y;\nsetp.ne.b32 p, 1, 0;\n"
        "add.u32 lo, %20, %21;\nmov.b64 y, {lo, 0x40000040};\n"
        "wgmma.mma_async.sync.aligned.m64n32k16.f32.bf16.bf16 "
        "{%0,%1,%2,%3,%4,%5,%6,%7,%8,%9,%10,%11,%12,%13,%14,%15}, {%16,%17,%18,%19}, y, p, 1, 1, 0;\n}\n"
        : "+f"(d[0]), "+f"(d[1]), "+f"(d[2]), "+f"(d[3]), "+f"(d[4]), "+f"(d[5]), "+f"(d[6]), "+f"(d[7]),
          "+f"(d[8]), "+f"(d[9]), "+f"(d[10]), "+f"(d[11]), "+f"(d[12]), "+f"(d[13]), "+f"(d[14]), "+f"(d[15])
        : "r"(a0), "r"(a1), "r"(a2), "r"(a3), "r"(dl), "n"(OB));
}
template <int KS> struct KgenSteps {
    static __device__ __forceinline__ void run(float (&d)[16], uint32_t dl) {
        KgenSteps<KS - 1>::run(d, dl);
        constexpr int k = KS - 1;
        wgmma_ss_n32<(k > 0), (O_H + (k / 4) * 3072 + (k % 4) * 32) / 16, (O_L + (k / 4) * 4096 + (k % 4) * 32) / 16>(d, dl);
    }
};
template <> struct KgenSteps<0> { static __device__ __forceinline__ void run(float (&)[16], uint32_t) {} };
template <int K0, int N, int I> struct NearSteps {
    static __device__ __forceinline__ void run(float (&d)[16], const uint4 (&f)[N], uint32_t dl) {
        NearSteps<K0, N, I - 1>::run(d, f, dl);
        constexpr int k = K0 + I - 1, dd = k / 4, kk = 4 * dd - (k - 3);
        wgmma_rs_n32<(O_U + (16 - dd) * 128 + kk * 32) / 16>(d, f[I - 1].x, f[I - 1].y, f[I - 1].z, f[I - 1].w, dl);
    }
};
template <int K0, int N> struct NearSteps<K0, N, 0> {
    static __device__ __forceinline__ void run(float (&)[16], const uint4 (&)[N], uint32_t) {}
};
template <int N>
__device__ __forceinline__ void load_toep(uint4 (&f)[N], uint32_t addr, uint32_t& prev) {
#pragma unroll
    for (int k = 0; k < N; k++)
    { const uint2 v = lds64(addr + k * 128); f[k].x = v.x; f[k].y = v.y; }
#pragma unroll
    for (int k = 0; k < N; k++) {
        f[k].z = prev;
        f[k].w = f[k].x;
        prev = f[k].y;
    }
}
__device__ __forceinline__ void mma16816(float (&d)[4], uint32_t a0, uint32_t a1, uint32_t a2, uint32_t b0,
                                         uint32_t b1) {
    asm("mma.sync.aligned.m16n8k16.row.col.f32.bf16.bf16.f32 {%0,%1,%2,%3}, {%4,%5,%6,%4}, {%7,%8}, {%0,%1,%2,%3};"
                 : "+f"(d[0]), "+f"(d[1]), "+f"(d[2]), "+f"(d[3])
                 : "r"(a0), "r"(a1), "r"(a2), "r"(b0), "r"(b1));
}
__device__ __forceinline__ uint4 ldsm_x4_t(uint32_t addr) {
    uint4 r;
    asm volatile("ldmatrix.sync.aligned.m8n8.x4.trans.shared.b16 {%0,%1,%2,%3}, [%4];"
                 : "=r"(r.x), "=r"(r.y), "=r"(r.z), "=r"(r.w) : "r"(addr));
    return r;
}
__device__ __forceinline__ int kc_index(int x) {
    const int i2 = 128 + ((x + ((x >> 1) & 1)) >> 1), i4 = 256 + ((x + 1 + ((x >> 2) & 1)) >> 2);
    return x < 256 ? x : (x < 512 ? i2 : i4);
}

struct Params { const bf16 *A_re, *A_im, *B_re, *B_im, *C_re, *C_im, *log_dt, *Dskip; };
struct ModeIn { float ar, ai, br, bi, cr, ci, ldt, dsk; };
__device__ __forceinline__ ModeIn load_mode(const Params& p, int d, int n) {
    ModeIn m;
    const int i = d * N_MODES + n;
    m.ar = __bfloat162float(p.A_re[i]); m.ai = __bfloat162float(p.A_im[i]);
    m.br = __bfloat162float(p.B_re[i]); m.bi = __bfloat162float(p.B_im[i]);
    m.cr = __bfloat162float(p.C_re[i]); m.ci = __bfloat162float(p.C_im[i]);
    m.ldt = __bfloat162float(p.log_dt[d]); m.dsk = __bfloat162float(p.Dskip[d]);
    return m;
}

__device__ __forceinline__ void gen_powers(const ModeIn& mi, uint32_t sb, int t) {
    const float dt = bf16r(expf(mi.ldt));
    const float lr = dt * mi.ar, li = dt * mi.ai;
    const float br = dt * mi.br, bi = dt * mi.bi;
    cplx c;
    c.r = mi.cr * br - mi.ci * bi;
    c.i = mi.cr * bi + mi.ci * br;
    const cplx z = cexp_l(lr, li, 1.f), wv = cexp_l(lr, li, 8.f), Z = cexp_l(lr, li, 256.f);
    const cplx z2 = cmul(z, z), z4 = cmul(z2, z2);
    const uint32_t x0 = ((t & 31) >> 2) * 16 + (t & 3) * 4;
    uint32_t xs[8];
#pragma unroll
    for (int j = 0; j < 8; j++) xs[j] = sb + (x0 ^ (j << 4));
    const uint32_t ho = O_H + (t >> 5) * 3072, lo_ = O_L + (t >> 5) * 4096;
#define PUT_H(row, v) sts32(xs[(row) & 7] + ho + (row) * 128, pack_bf16((v).r, -(v).i))
#define PUT_L(row, v) sts32(xs[(row) & 7] + lo_ + (row) * 128, pack_bf16((v).r, (v).i))
    cplx h = c;
    PUT_H(0, h);
#pragma unroll
    for (int k = 1; k < 8; k++) { h = cmul(h, z); PUT_H(k, h); }
    cplx hz = cmul(c, Z);
    PUT_H(8, hz);
    { cplx a = cmul(hz, z2); PUT_H(9, a); a = cmul(hz, z4); PUT_H(10, a); a = cmul(a, z2); PUT_H(11, a); }
    hz = cmul(hz, Z); PUT_H(12, hz);
    { cplx a = cmul(hz, z4); PUT_H(13, a); }
    hz = cmul(hz, Z); PUT_H(14, hz);
    { cplx a = cmul(hz, z4); PUT_H(15, a); }
#pragma unroll
    for (int k = 16; k < 21; k++) { hz = cmul(hz, Z); PUT_H(k, hz); }
    const cplx w2 = cmul(wv, wv);
    cplx le, lo = wv;
    le.r = 1.f; le.i = 0.f;
    PUT_L(0, le); PUT_L(1, lo);
#pragma unroll
    for (int k = 2; k < 32; k += 2) {
        le = cmul(le, w2); lo = cmul(lo, w2);
        PUT_L(k, le); PUT_L(k + 1, lo);
    }
}

__device__ __forceinline__ uint4 pack8(const float (&v)[8]) {
    return make_uint4(pack_bf16(v[0], v[1]), pack_bf16(v[2], v[3]), pack_bf16(v[4], v[5]), pack_bf16(v[6], v[7]));
}
__device__ __forceinline__ void st16B(uint32_t a, const uint4& v) { *sp<uint4>(a) = v; }

__device__ __forceinline__ void build_windows(uint32_t sb, int t) {
    if (t < 64) {
        const int which = t >> 4;
        sts128(sb + (which == 0 ? O_W1 : which == 1 ? O_W2 : which == 2 ? O_W3 : O_W4) - 256 + (t & 15) * 16, 0, 0, 0, 0);
    }
#pragma unroll
    for (int r = 0; r < 2; r++) {
        const int grp = t + r * 128;
        if (grp < 192) {
            const uint4 c0 = lds128(u_addr(sb, grp - 2)), c1 = lds128(u_addr(sb, grp - 1)), c2 = lds128(u_addr(sb, grp));
            float v[24];
            const uint32_t ww[12] = {c0.x, c0.y, c0.z, c0.w, c1.x, c1.y, c1.z, c1.w, c2.x, c2.y, c2.z, c2.w};
#pragma unroll
            for (int i = 2; i < 11; i++) { v[2 * i] = bf_lo(ww[i]); v[2 * i + 1] = bf_hi(ww[i]); }
            float p2[15];
#pragma unroll
            for (int j = 0; j < 15; j++) p2[j] = v[5 + j] + v[6 + j];
            float b1[8], b2[8];
#pragma unroll
            for (int i = 0; i < 8; i++) {
                b2[i] = p2[i + 6] + v[13 + i];
                b1[i] = p2[i + 1] + p2[i + 3] + v[10 + i];
            }
            st16B(sb + O_W1 + grp * 16, pack8(b1));
            st16B(sb + O_W2 + grp * 16, pack8(b2));
            if (r == 0) {
                float b3[8], b5[8];
#pragma unroll
                for (int i = 0; i < 8; i++) {
                    b3[i] = b1[i] + v[11 + i] + v[5 + i];
                    b5[i] = p2[i + 7];
                }
                st16B(sb + O_W3 + grp * 16, pack8(b3));
                st16B(sb + O_W5 + grp * 16, pack8(b5));
                st16B(sb + O_W4 + grp * 16, make_uint4(hadd2_bf(ww[6], ww[2]), hadd2_bf(ww[7], ww[3]),
                                                       hadd2_bf(ww[8], ww[4]), hadd2_bf(ww[9], ww[5])));
            }
        }
    }
}

__device__ __forceinline__ void build_tables(float (&kd)[16], float dskip, uint32_t sb, int t, int bar) {
    const int lane = t & 31, w = t >> 5, g = lane >> 2, tq = lane & 3;
    if (w == 0) {
        if (lane == 0) kd[0] += dskip;
        const uint32_t kn = sb + O_KN + 128;
#pragma unroll
        for (int j = 0; j < 4; j++) {
            const int lo = 8 * j + 2 * tq;
            const uint32_t p0 = pack_bf16(kd[4 * j], kd[4 * j + 1]), p1 = pack_bf16(kd[4 * j + 2], kd[4 * j + 3]);
            sts16(kn + (g + 8 * lo) * 2, p0);
            sts16(kn + (g + 8 * lo + 8) * 2, p0 >> 16);
            if (g < 4) {
#pragma unroll
                for (int e = 0; e < 2; e++) {
                    const uint32_t val = e ? (p1 >> 16) : p1, ad = kn + (256 + 2 * g + 8 * (lo + e)) * 2;
                    sts16(ad, val);
                    if (!(g & 1)) {
                        sts16(ad + 2, val);
                        if (g + lo + e > 0) sts16(ad - 2, val);
                    }
                }
            } else {
#pragma unroll
                for (int e = 0; e < 2; e++) {
                    const uint32_t val = e ? (p1 >> 16) : p1;
                    const int i8 = 64 + (g >= 6 ? 32 : 0) + lo + e;
                    if (j > 0 || i8 >= 66) {
                        sts16(sb + O_A12 + (i8 - 48) * 4 - ((g & 1) ? 0 : 2), val);
                    } else if (g & 1) {
                        sts16(kn + (8 * i8 + 3) * 2, val); sts16(kn + (8 * i8 + 4) * 2, val); sts16(kn + (8 * i8 + 5) * 2, val);
                    } else {
#pragma unroll
                        for (int dd = -2; dd <= 2; dd++)
                            if (i8 == 65 || dd >= -1) sts16(kn + (8 * i8 + dd) * 2, val);
                    }
                }
            }
        }
    } else if (w == 1) {
        if (g < 4) {
#pragma unroll
            for (int j = 0; j < 4; j++) {
                const int i8 = 128 + 32 * g + 8 * j + 2 * tq;
                const uint32_t p0 = pack_bf16(kd[4 * j], kd[4 * j + 1]);
                if (i8 == 128) { sts16(sb + O_A12 + (127 - 48) * 4 + 2, p0); sts16(sb + O_KQ, p0); }
                else sts16(sb + O_A3 + (i8 - 1 - 112) * 2, p0);
                sts16(sb + O_A3 + (i8 - 112) * 2, p0 >> 16);
            }
        } else if (lane == 16) {
            sts16(sb + O_A3 + (255 - 112) * 2, pack_bf16(kd[0], 0.f));
        }
    }
    wg_bar(bar);
    DBG1(4);
    {
#pragma unroll
        for (int r = 0; r < 2; r++) {
            const int i = t + r * 128;
            if (i < 160) {
                const uint32_t ka = sb + O_KN + (4 * i + 8) * 2;
                const uint32_t wm = lds32(ka - 4), w3 = lds32(ka + 12);
                const uint2 wa = lds64(ka), wb = lds64(ka + 16);
                const uint32_t w0 = wa.x, w1 = wa.y, w4 = wb.x, w5 = wb.y;
                sts128(sb + O_Q + i * 32, __byte_perm(w0, wm, 0x7610), __byte_perm(w4, w3, 0x7610),
                       __byte_perm(w0, w0, 0x1032), __byte_perm(w4, w4, 0x1032));
                sts128(sb + O_Q + i * 32 + 16, __byte_perm(w1, w0, 0x7610), __byte_perm(w5, w4, 0x7610),
                       __byte_perm(w1, w1, 0x1032), __byte_perm(w5, w5, 0x1032));
            }
        }
        {
            const uint32_t aa = sb + O_A3 + (8 + t) * 2;
            const uint32_t p0 = lds16(aa) | (lds16(aa - 2) << 16), p1 = lds16(aa + 16) | (lds16(aa + 14) << 16);
            const uint32_t msk = (t & 1) ? 0x0000ffffu : 0xffff0000u;
            sts128(sb + O_Q34 + t * 16, p0, p1, p0 & msk, p1 & msk);
        }
        if (t >= 48) {
            const uint32_t aa = sb + O_A12 + (t - 48 + 8) * 4;
            const uint32_t e0 = lds32(aa), e1 = lds32(aa - 4), f0 = lds32(aa + 32), f1 = lds32(aa + 28);
            sts128(sb + O_Q12 + (t - 48) * 16, __byte_perm(e0, e1, 0x7632), __byte_perm(f0, f1, 0x7632),
                   __byte_perm(e0, e1, 0x5410), __byte_perm(f0, f1, 0x5410));
        }
    }
}

__device__ __forceinline__ void convolve(int d, uint32_t sb, int t, int bar, const CUtensorMap* tmo) {
    const int lane = t & 31, w = t >> 5, g = lane >> 2, tq = lane & 3;
    const uint32_t dl = (sb & 0x3FFFF) >> 4;
    float y[16];
#pragma unroll
    for (int i = 0; i < 16; i++) y[i] = 0.f;
    {
        const uint32_t qa = sb + O_Q + (16 * w + g - 2 * tq + 56 - 48) * 8;
        uint32_t prev = 0;
#define NEAR_BATCH(N, K0)                              \
        { uint4 F[N];                                  \
          load_toep<N>(F, qa + (K0) * 128, prev);      \
          WG_FENCE();                                  \
          NearSteps<K0, N, N>::run(y, F, dl);          \
          WG_COMMIT(); }
        NEAR_BATCH(5, 0)
        NEAR_BATCH(4, 5)
        WG_WAIT(1);
        NEAR_BATCH(4, 9)
        WG_WAIT(1);
        NEAR_BATCH(4, 13)
        WG_WAIT(1);
        NEAR_BATCH(4, 17)
        WG_WAIT(1);
        NEAR_BATCH(4, 21)
        WG_WAIT(1);
        NEAR_BATCH(4, 25)
        WG_WAIT(1);
        NEAR_BATCH(4, 29)
        WG_WAIT(1);
        NEAR_BATCH(4, 33)
        WG_WAIT(0);
#pragma unroll
        for (int i = 0; i < 16; i++) asm volatile("" : "+f"(y[i])::"memory");
    }
    DBG1(6);
    {
        const int par = w & 1;
        const uint32_t qoff = sb + (g - 2 * tq) * 16;
        const uint32_t roff = sb + (lane & 15) * 16 + par * 256;
        const uint32_t yoff = sb + (136 * par + 8 * g + 2 * tq) * 4;
        if (w < 2) {
            const uint32_t wb = roff + ((lane >> 4) ? O_W2 : O_W1);
            uint4 f[5];
#pragma unroll
            for (int q = 4; q <= 8; q++) f[q - 4] = lds128(qoff + O_Q12 + (16 * q - 56) * 16);
            uint4 bt[12];
#pragma unroll
            for (int i = 0; i < 6; i++) {
                if (i == 0) bt[0] = ldsm_x4_t(wb - 256);
                bt[2 * i + 1] = ldsm_x4_t(wb + (2 * i) * 256);
                if (i > 0) bt[2 * i] = ldsm_x4_t(wb + (2 * i - 1) * 256);
                float a0[4] = {0.f, 0.f, 0.f, 0.f}, a1[4] = {0.f, 0.f, 0.f, 0.f};
#pragma unroll
                for (int q = 4; q <= 8; q++) {
                    const int k = 2 * i + 4 - q;
                    if (k >= -1) {
                        mma16816(a0, f[q - 4].x, f[q - 4].y, q > 4 ? f[q > 4 ? q - 5 : 0].y : 0u, bt[k + 1].x, bt[k + 1].y);
                        mma16816(a1, f[q - 4].z, f[q - 4].w, q > 4 ? f[q > 4 ? q - 5 : 0].w : 0u, bt[k + 1].z, bt[k + 1].w);
                    }
                }
                const uint32_t ya = yoff + O_Y12 + 136 * (4 + 2 * i) * 4;
                sts64f(ya, a0[0] + a1[0], a0[1] + a1[1]);
                sts64f(ya + 256, a0[2] + a1[2], a0[3] + a1[3]);
            }
        } else {
            const uint32_t wb = roff + ((lane >> 4) ? O_W4 : O_W3);
            uint4 bt[8];
#pragma unroll
            for (int k = 0; k < 8; k++) bt[k] = ldsm_x4_t(wb + (k - 1) * 256);
            const uint4 b5a = ldsm_x4_t(roff + O_W5 + (lane >> 4) * 512), b5b = ldsm_x4_t(roff + O_W5 + 1024 + (lane >> 4) * 512);
            const uint32_t kq = lds16(sb + O_KQ);
            const uint32_t dg = (g == 2 * tq) ? kq : ((g == 2 * tq + 1) ? (kq << 16) : 0u);
            float acc[4][4];
#pragma unroll
            for (int i = 0; i < 4; i++)
#pragma unroll
                for (int j = 0; j < 4; j++) acc[i][j] = 0.f;
            mma16816(acc[0], dg, 0u, 0u, b5a.x, b5a.y);
            mma16816(acc[1], dg, 0u, 0u, b5a.z, b5a.w);
            mma16816(acc[2], dg, 0u, 0u, b5b.x, b5b.y);
            mma16816(acc[3], dg, 0u, 0u, b5b.z, b5b.w);
            uint32_t pa = 0, pb = 0;
#pragma unroll
            for (int q = 8; q <= 15; q++) {
                const uint4 f = lds128(qoff + O_Q34 + (16 * q - 120) * 16);
#pragma unroll
                for (int i = 0; i < 4; i++) {
                    const int k = 2 * i + 8 - q;
                    if (k >= -1) mma16816(acc[i], f.x, f.y, pa, bt[k + 1].x, bt[k + 1].y);
                }
#pragma unroll
                for (int i = 0; i < 4; i++) {
                    const int k = 2 * i + 8 - q;
                    if (k >= -1) mma16816(acc[i], f.z, f.w, pb, bt[k + 1].z, bt[k + 1].w);
                }
                pa = f.y; pb = f.w;
            }
#pragma unroll
            for (int i = 0; i < 4; i++) {
                const uint32_t ya = yoff + O_Y34 + 136 * (8 + 2 * i) * 4;
                sts64f(ya, acc[i][0], acc[i][1]);
                sts64f(ya + 256, acc[i][2], acc[i][3]);
            }
        }
    }
    wg_bar(bar);
    DBG1(7);
    {
        const uint32_t yb = sb + (136 * tq + 16 * w + g) * 4;
#pragma unroll
        for (int j = 1; j < 4; j++)
#pragma unroll
            for (int e = 0; e < 4; e++) {
                const uint32_t o = yb + (544 * j + 64 * (e & 1) + 8 * (e >> 1)) * 4;
                y[4 * j + e] += ldsf(o + O_Y12);
                if (j >= 2) y[4 * j + e] += ldsf(o + O_Y34);
            }
#pragma unroll
        for (int jp = 0; jp < 2; jp++) {
            const int a = 8 * (2 * jp + (lane >> 4)) + (lane & 7);
            const uint32_t addr = sb + O_ST + a * 128 + (((2 * w + ((lane >> 3) & 1)) ^ (lane & 7)) << 4);
            asm volatile("stmatrix.sync.aligned.m8n8.x4.trans.shared.b16 [%0], {%1,%2,%3,%4};" ::"r"(addr),
                         "r"(pack_bf16(y[8 * jp + 0], y[8 * jp + 1])), "r"(pack_bf16(y[8 * jp + 2], y[8 * jp + 3])),
                         "r"(pack_bf16(y[8 * jp + 4], y[8 * jp + 5])), "r"(pack_bf16(y[8 * jp + 6], y[8 * jp + 7]))
                         : "memory");
        }
        asm volatile("fence.proxy.async.shared::cta;" ::: "memory");
        wg_bar(bar);
        if (t == 0) {
            asm volatile("cp.async.bulk.tensor.2d.global.shared::cta.bulk_group [%0, {%1, %2}], [%3];"
                         ::"l"(tmo), "r"(0), "r"(d * 32), "r"(sb + O_ST) : "memory");
            asm volatile("cp.async.bulk.commit_group;" ::: "memory");
            asm volatile("cp.async.bulk.wait_group 0;" ::: "memory");
        }
        DBG1(8);
    }
}

constexpr int K1_WGS = 5;
constexpr int O_XTRA = K1_WGS * WG_BYTES;
constexpr int K1_SMEM = O_XTRA + 3 * 4096;
constexpr int K1_CTAS = (D_MODEL + K1_WGS - 1) / K1_WGS;
__device__ __forceinline__ uint32_t raw_box(uint32_t sbase, int i) {
    return i < K1_WGS ? sbase + i * WG_BYTES + O_RAW : sbase + O_XTRA + (i - K1_WGS) * 4096;
}
__device__ __forceinline__ void transpose_window(uint32_t sbase, int warp, int lane, int ch0) {
    const int ch = (lane >> 2) + ch0;
    const uint32_t ub = sbase + ch * WG_BYTES + (lane & 3) * 4;
#pragma unroll
    for (int k = 0; k < 4; k++) {
        const int gi = warp + k * (4 * K1_WGS);
        if (gi < 64) {
            const uint4 v = ldsm_x4_t(raw_box(sbase, gi >> 3) + (gi & 7) * 512 + lane * 16);
            if (ch >= 0 && ch < K1_WGS) {
                const uint32_t a0 = u_addr(ub, 4 * gi);
                sts32(a0, v.x);
                sts32(a0 ^ 16, v.y);
                sts32(a0 ^ 32, v.z);
                sts32(a0 ^ 48, v.w);
            }
        }
    }
}

__global__ void __launch_bounds__(128 * K1_WGS, 1)
ssm_kernel(const __grid_constant__ CUtensorMap tmc, const __grid_constant__ CUtensorMap tmo,
           const bf16* __restrict__ x, const bf16* __restrict__ gw, Params p) {
    extern __shared__ __align__(1024) uint8_t smem_raw[];
    const uint32_t sbase = smem_u32(smem_raw);
    const int tid = threadIdx.x, t = tid & 127, lane = tid & 31;
    const int wg = __shfl_sync(0xffffffffu, tid >> 7, 0), warp = __shfl_sync(0xffffffffu, tid >> 5, 0);
    const int d0 = blockIdx.x * K1_WGS, d = min(d0 + wg, D_MODEL - 1);
    const uint32_t sb = sbase + wg * WG_BYTES;
    const uint32_t xbar = sbase + WG_BYTES - 16;
    const int dw = d0 & ~7;
    const bool two = (d0 & 7) > 3 && dw + 8 < D_MODEL;
    DBG1(0);
    asm volatile("griddepcontrol.launch_dependents;");
    if (tid == 0) {
        mbar_init(xbar, 1);
        asm volatile("fence.mbarrier_init.release.cluster;" ::: "memory");
        mbar_expect(xbar, 8 * 4096);
#pragma unroll
        for (int i = 0; i < 8; i++) tma2d(raw_box(sbase, i), &tmc, dw, i * 256, xbar);
        if (blockIdx.x == 0) g_epoch = g_epoch + 1;
    }
    const ModeIn mi = load_mode(p, d, t);
    const int row = min(blockIdx.x * (4 * K1_WGS) + warp, L_SEQ - 1);
    uint32_t xr[9], gr[9];
#pragma unroll
    for (int i = 0; i < 9; i++) {
        xr[i] = __ldg(reinterpret_cast<const uint32_t*>(x + (size_t)row * D_MODEL) + lane + 32 * i);
        gr[i] = __ldg(reinterpret_cast<const uint32_t*>(gw) + lane + 32 * i);
    }
    sts128(sb + O_U + t * 16, 0, 0, 0, 0);
    sts128(sb + O_KN + t * 16, 0, 0, 0, 0);
    gen_powers(mi, sb, t);
    DBG1(1);
    asm volatile("fence.proxy.async.shared::cta;" ::: "memory");
    __syncthreads();
    float kd[16];
    WG_FENCE();
    KgenSteps<16>::run(kd, (sb & 0x3FFFF) >> 4);
    WG_COMMIT();
    mbar_wait(xbar, 0);
    DBG1(2);
    transpose_window(sbase, warp, lane, dw - d0);
    if (two) {
        asm volatile("fence.proxy.async.shared::cta;" ::: "memory");
        __syncthreads();
        if (tid == 0) {
            mbar_expect(xbar, 8 * 4096);
#pragma unroll
            for (int i = 0; i < 8; i++) tma2d(raw_box(sbase, i), &tmc, dw + 8, i * 256, xbar);
        }
    }
    {
        float s = 0.f, gs = 0.f;
#pragma unroll
        for (int i = 0; i < 9; i++) {
            s += bf_lo(xr[i]) + bf_hi(xr[i]);
            const uint32_t pr = hmul2_bf(xr[i], gr[i]);
            gs += bf_lo(pr) + bf_hi(pr);
        }
#pragma unroll
        for (int o = 16; o; o >>= 1) {
            s += __shfl_xor_sync(~0u, s, o);
            gs += __shfl_xor_sync(~0u, gs, o);
        }
        const float mean = s * (1.f / D_MODEL);
        float q = 0.f;
#pragma unroll
        for (int i = 0; i < 9; i++) {
            const float a = bf_lo(xr[i]) - mean, b = bf_hi(xr[i]) - mean;
            q = fmaf(a, a, fmaf(b, b, q));
        }
#pragma unroll
        for (int o = 16; o; o >>= 1) q += __shfl_xor_sync(~0u, q, o);
        if (lane == 0) {
            const float var = bf16r(q * (1.f / D_MODEL));
            const float den = bf16r(sqrtf(bf16r(var + 1e-5f)));
            g_rowstat[row] = make_uint2(pack_bf16(mean, mean), __float_as_uint(__fdividef(1.f, den)));
            g_gate[row] = bf16r(__fdividef(1.f, 1.f + __expf(-bf16r(gs))));
        }
    }
    DBG1(3);
    WG_WAIT(0);
#pragma unroll
    for (int i = 0; i < 16; i++) asm volatile("" : "+f"(kd[i])::"memory");
    build_tables(kd, mi.dsk, sb, t, 1 + wg);
    if (two) {
        mbar_wait(xbar, 1);
        transpose_window(sbase, warp, lane, dw + 8 - d0);
    }
    asm volatile("fence.proxy.async.shared::cta;" ::: "memory");
    __syncthreads();
    DBG1(5);
    build_windows(sb, t);
    wg_bar(1 + wg);
    DBG1(9);
    if (d0 + wg < D_MODEL) convolve(d, sb, t, 1 + wg, &tmo);
}
}

constexpr int XT_BYTES = 128 * D_MODEL * 2;
constexpr int STAGE_BYTES = 96 * 128;
constexpr int NSTAGE = 6;
constexpr int SM_STAGES = XT_BYTES;
constexpr int SM_BARS = SM_STAGES + NSTAGE * STAGE_BYTES;
constexpr int SM_B1 = SM_BARS + 512;
constexpr int SM_B2 = SM_B1 + 576 * 4;
constexpr int MLP_SMEM = SM_B2 + 576 * 2;
constexpr int BAR_FULL = 0, BAR_EMPTY = 48, BAR_X = 96, BAR_PARKFREE = 168, BAR_STORED = 176, BAR_LOADED = 248, BAR_A = 320;

__device__ __forceinline__ float gelu2(float x) {
    const float k0 = 0.7978845608028654f, k1 = 0.7978845608028654f * 0.044715f;
    float u = x * fmaf(x * x, k1, k0);
    float th;
    asm("tanh.approx.f32 %0, %1;" : "=f"(th) : "f"(u));
    return fmaf(x, th, x);
}

__device__ __forceinline__ void epi_gelu(const float (&acc)[32], int i, uint32_t b1_addr, float r0, float r1,
                                         uint32_t (&o)[4]) {
    float b0, b1, b2, b3;
    asm volatile("ld.shared.v4.f32 {%0,%1,%2,%3}, [%4];"
                 : "=f"(b0), "=f"(b1), "=f"(b2), "=f"(b3) : "r"(b1_addr + i * 16));
    o[0] = pack_bf16(gelu2(fmaf(acc[8 * i + 0], r0, b0)), gelu2(fmaf(acc[8 * i + 1], r0, b1)));
    o[1] = pack_bf16(gelu2(fmaf(acc[8 * i + 2], r1, b0)), gelu2(fmaf(acc[8 * i + 3], r1, b1)));
    o[2] = pack_bf16(gelu2(fmaf(acc[8 * i + 4], r0, b2)), gelu2(fmaf(acc[8 * i + 5], r0, b3)));
    o[3] = pack_bf16(gelu2(fmaf(acc[8 * i + 6], r1, b2)), gelu2(fmaf(acc[8 * i + 7], r1, b3)));
}
__device__ __forceinline__ void epi_park(const float (&acc)[32], int i, uint32_t b1_addr, uint32_t park_addr,
                                         float r0, float r1) {
    uint32_t o[4];
    epi_gelu(acc, i, b1_addr, r0, r1, o);
    asm volatile("st.shared.v4.b32 [%0], {%1,%2,%3,%4};" ::"r"(park_addr + i * 4096), "r"(o[0]), "r"(o[1]),
                 "r"(o[2]), "r"(o[3]) : "memory");
}
__device__ __forceinline__ void epi_part(const float (&acc)[32], int i, uint4* part, uint32_t par) {
    uint4 v;
    v.x = (pack_bf16(acc[8 * i + 0], acc[8 * i + 1]) & ~1u) | par;
    v.y = pack_bf16(acc[8 * i + 2], acc[8 * i + 3]);
    v.z = (pack_bf16(acc[8 * i + 4], acc[8 * i + 5]) & ~1u) | par;
    v.w = pack_bf16(acc[8 * i + 6], acc[8 * i + 7]);
    asm volatile("{\n.reg .b128 q;\nmov.b128 q, {%1, %2};\nst.relaxed.gpu.global.b128 [%0], q;\n}\n" ::"l"(part + i * 32),
                 "l"(((unsigned long long)v.y << 32) | v.x), "l"(((unsigned long long)v.w << 32) | v.z) : "memory");
}
__device__ __forceinline__ void warp_arrive(uint32_t bar, int lane) {
    __syncwarp();
    if (lane == 0) asm volatile("mbarrier.arrive.shared::cta.b64 _, [%0];" ::"r"(bar) : "memory");
}

__device__ __forceinline__ void probe_partials(const uint4* unit, uint32_t par) {
    asm volatile(
        "{\n.reg .pred p;\n.reg .u32 n, v;\nmov.u32 n, 0;\n"
        "PROBE_LOOP:\n"
        "ld.relaxed.gpu.global.u32 v, [%0];\n"
        "xor.b32 v, v, %1;\n"
        "and.b32 v, v, 1;\n"
        "setp.ne.u32 p, v, 0;\n"
        "vote.sync.any.pred p, p, 0xffffffff;\n"
        "@!p bra PROBE_DONE;\n"
        "add.u32 n, n, 1;\n"
        "setp.lt.u32 p, n, 1048576;\n"
        "@p bra PROBE_LOOP;\n"
        "trap;\n"
        "PROBE_DONE:\n}\n" ::"l"(unit), "r"(par) : "memory");
}

template <int EPI>
__device__ __forceinline__ void run_chunk(float (&cur)[32], float (&prev)[32], const uint32_t (&af)[NAF][4],
                                          int parity, uint32_t bars, uint32_t desc0, uint32_t adesc0, uint32_t p0, uint32_t p1,
                                          uint4* part, bool sig, uint32_t rbar, int lane, float r0, float r1) {
#pragma unroll
    for (int s = 0; s < 6; s++) {
        mbar_wait(bars + BAR_FULL + s * 8, parity);
        WG_FENCE();
        mma_stage_rt(s, cur, af, desc0, adesc0);
        WG_COMMIT();
        if (s >= 1 && s <= 4) {
            if (EPI == 1) epi_park(prev, s - 1, p0, p1, r0, r1);
            if (EPI == 2) epi_part(prev, s - 1, part, p1);
        }
        if (s == 4 && EPI == 2) warp_arrive(p0, lane);
        WG_WAIT(1);
        if (sig) asm volatile("mbarrier.arrive.shared::cluster.b64 _, [%0];" ::"r"(rbar + ((s + 5) % 6) * 8) : "memory");
        if (s == 0) fence_acc(prev);
    }
}

__global__ void __cluster_dims__(2, 1, 1) __launch_bounds__(384, 1)
mlp_kernel(const __grid_constant__ CUtensorMap tmx, const __grid_constant__ CUtensorMap tmw1,
           const __grid_constant__ CUtensorMap tmw2, const __grid_constant__ CUtensorMap tma,
           const bf16* __restrict__ b1, const bf16* __restrict__ b2,
           bf16* __restrict__ out) {
    extern __shared__ __align__(1024) uint8_t smem_raw[];
    const uint32_t sbase = smem_u32(smem_raw);
    uint8_t* sgen = smem_raw;
    const int tid = threadIdx.x, lane = tid & 31;
    const int warp = __shfl_sync(0xffffffffu, tid >> 5, 0);
    const int wgid = __shfl_sync(0xffffffffu, tid >> 7, 0);
    const int m = blockIdx.x & 15, f = blockIdx.x >> 4;
    const uint32_t rank = m & 1;
    const uint32_t bars = sbase + SM_BARS;
    if (warp == 0) DBG(12);

    if (tid == 0) {
        if (sbase & 1023) asm volatile("trap;");
        for (int i = 0; i < NSTAGE; i++) {
            mbar_init(bars + BAR_FULL + i * 8, 1);
            mbar_init(bars + BAR_EMPTY + i * 8, 4);
        }
        for (int i = 0; i < 9; i++) mbar_init(bars + BAR_X + i * 8, 1);
        mbar_init(bars + BAR_PARKFREE, 8);
        mbar_init(bars + BAR_A, 1);
        for (int i = 0; i < 9; i++) {
            mbar_init(bars + BAR_STORED + i * 8, 8);
            mbar_init(bars + BAR_LOADED + i * 8, 1);
        }
        asm volatile("fence.mbarrier_init.release.cluster;" ::: "memory");
        for (int j = 0; j < 9; j++) {
            mbar_expect(bars + BAR_X + j * 8, 16384);
            tma2d(sbase + j * 16384, &tmx, j * 64, m * 128, bars + BAR_X + j * 8);
        }
    }
    uint32_t b1v0 = 0, b1v1 = 0;
    uint2 rs0 = make_uint2(0, 0), rs1 = rs0;
    if (wgid < 2) {
        const uint32_t* b1w = reinterpret_cast<const uint32_t*>(b1 + f * 576);
        b1v0 = __ldg(b1w + (tid >> 5) * 32 + (tid & 7) * 4 + ((tid >> 3) & 3));
        if (tid < 32) b1v1 = __ldg(b1w + 8 * 32 + (tid & 7) * 4 + ((tid >> 3) & 3));
        asm volatile("griddepcontrol.wait;" ::: "memory");
        rs0 = __ldcg(&g_rowstat[m * 128 + warp * 16 + (lane >> 2)]);
        rs1 = __ldcg(&g_rowstat[m * 128 + warp * 16 + (lane >> 2) + 8]);
    }
    __syncthreads();
    asm volatile("barrier.cluster.arrive.relaxed.aligned;\nbarrier.cluster.wait.aligned;" ::: "memory");

    if (warp == 0) DBG(0);
    if (wgid == 2) {
        asm volatile("setmaxnreg.dec.sync.aligned.u32 40;");
        if (warp == 8) {
            if (lane == 0) {
                const uint32_t dst0 = sbase + SM_STAGES + rank * (STAGE_BYTES / 2);
#pragma unroll 1
                for (int cc = 0; cc < 18; cc++) {
                    const CUtensorMap* tm = cc < 9 ? &tmw1 : &tmw2;
                    const int c0 = cc < 9 ? f * 576 + cc * 64 : (cc - 9) * 64;
                    const int c1 = (cc < 9 ? 0 : f * 576) + rank * 48;
                    const int par = (cc & 1) ^ 1;
#pragma unroll
                    for (int s = 0; s < 6; s++) {
                        mbar_wait(bars + BAR_EMPTY + s * 8, par);
                        mbar_expect(bars + BAR_FULL + s * 8, STAGE_BYTES);
                        tma2d_mc(dst0 + s * STAGE_BYTES, tm, c0, c1 + s * 96, bars + BAR_FULL + s * 8, 3);
                    }
                }
                asm volatile("griddepcontrol.wait;" ::: "memory");
                mbar_wait(bars + BAR_EMPTY + 0, 1);
                mbar_wait(bars + BAR_EMPTY + 8, 1);
                mbar_expect(bars + BAR_A, 576 * 32);
#pragma unroll
                for (int q = 0; q < 3; q++)
                    tma2d(sbase + SM_STAGES + q * 6144, &tma, m * 128 + f * 16, q * 192, bars + BAR_A);
            }
        } else if (warp == 9) {
            {
                uint32_t* b2s = reinterpret_cast<uint32_t*>(sgen + SM_B2);
                for (int w = lane; w < 288; w += 32) {
                    const int jj = w & 1, q = (w >> 1) & 3, ci = w >> 3;
                    b2s[w] = __ldg(reinterpret_cast<const uint32_t*>(b2) + ci * 8 + jj * 4 + q);
                }
                __syncwarp();
            }
            asm volatile("griddepcontrol.wait;" ::: "memory");
            const uint32_t par = __ldcg(&g_epoch);
            mbar_wait(bars + BAR_PARKFREE, 0);
            asm volatile("fence.proxy.async.shared::cta;" ::: "memory");
            const uint4* psrc = g_part + (m * 9 * 8 + f) * (8 * 4 * 32);
#pragma unroll 1
            for (int c = 0; c < 9; c++) {
                mbar_wait(bars + BAR_STORED + c * 8, 0);
                probe_partials(psrc + (lane & 7) * 128 + 96 + 31, par);
                DBG(16 + c);
                if (lane == 0) {
                    mbar_expect(bars + BAR_LOADED + c * 8, 16384);
                    asm volatile("cp.async.bulk.shared::cluster.global.mbarrier::complete_tx::bytes [%0], [%1], 16384, [%2];"
                                 ::"r"(sbase + c * 16384), "l"(psrc), "r"(bars + BAR_LOADED + c * 8) : "memory");
                }
                psrc += 8 * 8 * 4 * 32;
            }
        }
        __syncwarp();
        asm volatile("barrier.cluster.arrive.release.aligned;\nbarrier.cluster.wait.acquire.aligned;" ::: "memory");
    } else {
        asm volatile("setmaxnreg.inc.sync.aligned.u32 232;");
        const int g = lane >> 2, tq = lane & 3;
        uint32_t af[NAF][4];
        float acc0[32], acc1[32];
        const bool sig = (tid & 127) < 2;
        uint32_t rbar;
        asm volatile("mapa.shared::cluster.u32 %0, %1, %2;" : "=r"(rbar) : "r"(bars + BAR_EMPTY), "r"(tid & 1));
        const uint32_t desc0 = ((sbase + SM_STAGES) & 0x3FFFF) >> 4;
        const uint32_t adesc0 = ((sbase + 8 * 16384 + wgid * 8192) & 0x3FFFF) >> 4;

        {
            float2* b1s = reinterpret_cast<float2*>(sgen + SM_B1);
            b1s[tid] = make_float2(bf_lo(b1v0), bf_hi(b1v0));
            if (tid < 32) b1s[256 + tid] = make_float2(bf_lo(b1v1), bf_hi(b1v1));
        }
        {
            const int lrow = warp * 16 + (lane & 7) + ((lane >> 3) & 1) * 8;
            const uint32_t rbase = sbase + lrow * 128;
            const int hi = lane >> 4, sw = lrow & 7;
#pragma unroll
            for (int j = 0; j < 9; j++) {
                mbar_wait(bars + BAR_X + j * 8, 0);
                if (warp == 0 && (j == 0 || j == 4 || j == 8)) DBG(44 + j / 4);
#pragma unroll
                for (int kk = 0; kk < 4; kk++) {
                    uint32_t tmp[4];
                    uint32_t (&a)[4] = (j * 4 + kk < NAF) ? af[(j * 4 + kk < NAF) ? j * 4 + kk : 0] : tmp;
                    const uint32_t addr = rbase + j * 16384 + (((kk * 2 + hi) ^ sw) << 4);
                    ldsm_x4(a, addr);
                    a[0] = hsub2_bf(a[0], rs0.x);
                    a[1] = hsub2_bf(a[1], rs1.x);
                    a[2] = hsub2_bf(a[2], rs0.x);
                    a[3] = hsub2_bf(a[3], rs1.x);
                    if (j * 4 + kk >= NAF) stsm_x4(a, addr);
                }
            }
            asm volatile("fence.proxy.async.shared::cta;" ::: "memory");
            asm volatile("bar.sync %0, 128;" ::"r"(3 + wgid) : "memory");
        }
        const float rstd0 = __uint_as_float(rs0.y), rstd1 = __uint_as_float(rs1.y);
        if (warp == 0) DBG(1);
        {
#pragma unroll
            for (int s = 0; s < 6; s++) {
                mbar_wait(bars + BAR_FULL + s * 8, 0);
                WG_FENCE();
                mma_stage_rt(s, acc0, af, desc0, adesc0);
                WG_COMMIT();
                if (s > 0) {
                    WG_WAIT(1);
                    if (sig) asm volatile("mbarrier.arrive.shared::cluster.b64 _, [%0];" ::"r"(rbar + (s - 1) * 8) : "memory");
                }
            }
            asm volatile("bar.sync 1, 256;" ::: "memory");
        }
        {
            uint32_t b1a = sbase + SM_B1 + tq * 64, park = sbase + tid * 16;
#pragma unroll 1
            for (int c = 1; c < 9; c += 2) {
                if (warp == 0) DBG(2 + (c >> 1));
                run_chunk<1>(acc1, acc0, af, 1, bars, desc0, adesc0, b1a, park, nullptr, sig, rbar, lane, rstd0, rstd1);
                run_chunk<1>(acc0, acc1, af, 0, bars, desc0, adesc0, b1a + 256, park + 16384, nullptr, sig, rbar, lane, rstd0, rstd1);
                b1a += 512;
                park += 32768;
            }
        }
        if (warp == 0) DBG(6);
        WG_WAIT(0);
        if (sig) asm volatile("mbarrier.arrive.shared::cluster.b64 _, [%0];" ::"r"(rbar + 5 * 8) : "memory");
        fence_acc(acc0);
#pragma unroll
        for (int k = 0; k < 32; k++)
            asm volatile("ld.shared.v4.b32 {%0,%1,%2,%3}, [%4];"
                         : "=r"(af[k][0]), "=r"(af[k][1]), "=r"(af[k][2]), "=r"(af[k][3])
                         : "r"(sbase + tid * 16 + k * 4096) : "memory");
        {
#pragma unroll
            for (int s = 0; s < 6; s++) {
                mbar_wait(bars + BAR_FULL + s * 8, 1);
                WG_FENCE();
                mma_stage_rt(s, acc1, af, desc0, adesc0);
                WG_COMMIT();
                if (s < 2) epi_gelu(acc0, s, sbase + SM_B1 + tq * 64 + 8 * 256, rstd0, rstd1, af[32 + (s & 1)]);
                if (s == 2 || s == 3) {
                    uint32_t tmp[4];
                    epi_gelu(acc0, s, sbase + SM_B1 + tq * 64 + 8 * 256, rstd0, rstd1, tmp);
                    const int lrow = warp * 16 + (lane & 7) + ((lane >> 3) & 1) * 8;
                    stsm_x4(tmp, sbase + 8 * 16384 + lrow * 128 + (((s * 2 + (lane >> 4)) ^ (lrow & 7)) << 4));
                }
                if (s == 3) {
                    asm volatile("fence.proxy.async.shared::cta;" ::: "memory");
                    asm volatile("bar.sync %0, 128;" ::"r"(3 + wgid) : "memory");
                }
                if (s > 0) {
                    WG_WAIT(1);
                    if (sig) asm volatile("mbarrier.arrive.shared::cluster.b64 _, [%0];" ::"r"(rbar + (s - 1) * 8) : "memory");
                }
                if (s == 5) warp_arrive(bars + BAR_PARKFREE, lane);
            }
        }
        uint4* part = g_part + (size_t)((m * 9 * 8 + warp) * 8 + f) * (4 * 32) + lane;
        uint32_t stored = bars + BAR_STORED;
        const uint32_t par = __ldcg(&g_epoch) & 1u;
#pragma unroll 1
        for (int c = 1; c < 9; c += 2) {
            if (warp == 0) DBG(7 + (c >> 1));
            run_chunk<2>(acc0, acc1, af, 0, bars, desc0, adesc0, stored, par, part, sig, rbar, lane, 0.f, 0.f);
            run_chunk<2>(acc1, acc0, af, 1, bars, desc0, adesc0, stored + 8, par, part + 8 * 8 * 4 * 32, sig, rbar, lane, 0.f, 0.f);
            part += 2 * 8 * 8 * 4 * 32;
            stored += 16;
        }
        const int t0 = m * 128 + f * 16 + g;
        const float g0 = __ldcg(&g_gate[t0]), g1 = __ldcg(&g_gate[t0 + 8]);
        WG_WAIT(0);
        fence_acc(acc1);
#pragma unroll
        for (int i = 0; i < 4; i++) epi_part(acc1, i, part, par);
        warp_arrive(stored, lane);
        if (warp == 0) DBG(11);
        {
            const uint32_t gA = pack_bf16(g0, g0), gB = pack_bf16(g1, g1);
            const uint32_t half2 = 0x3f003f00u, one2 = 0x3f803f80u;
            const uint32_t oA = hsub2_bf(one2, gA), oB = hsub2_bf(one2, gB);
            uint32_t* o32 = reinterpret_cast<uint32_t*>(out + (size_t)t0 * D_MODEL + 2 * tq) + warp * 4;
            const uint32_t lm = sbase + SM_STAGES + (lane & 7) * 32 + ((lane >> 3) & 1) * 16 + warp * 256;
            const uint32_t a0 = sbase + (warp >> 1) * 512 + lane * 16 + (warp & 1) * 8;
            const uint32_t b2a = sbase + SM_B2 + (warp >> 1) * 32 + tq * 8 + (warp & 1) * 4;
            mbar_wait(bars + BAR_A, 0);
#pragma unroll
            for (int grp = 0; grp < 3; grp++) {
                constexpr int NC = 4;
                const int c0 = grp * 4;
                uint2 v[NC][8], av[NC];
                uint32_t bb[NC];
#pragma unroll
                for (int k = 0; k < NC; k++) {
                    const int c = c0 + k;
                    if (c < 9) {
                        mbar_wait(bars + BAR_LOADED + c * 8, 0);
#pragma unroll
                        for (int q = 0; q < 8; q++)
                            asm volatile("ld.shared.v2.b32 {%0,%1}, [%2];" : "=r"(v[k][q].x), "=r"(v[k][q].y)
                                         : "r"(a0 + c * 16384 + q * 2048) : "memory");
                        asm volatile("ldmatrix.sync.aligned.m8n8.x2.trans.shared.b16 {%0,%1}, [%2];"
                                     : "=r"(av[k].x), "=r"(av[k].y) : "r"(lm + c * 2048) : "memory");
                        asm volatile("ld.shared.b32 %0, [%1];" : "=r"(bb[k]) : "r"(b2a + c * 128) : "memory");
                    }
                }
#pragma unroll
                for (int k = 0; k < NC; k++) {
                    const int c = c0 + k;
                    if (c < 9) {
                        int tries = 0;
                        while (true) {
                            uint32_t bad = 0;
#pragma unroll
                            for (int q = 0; q < 8; q++) bad |= v[k][q].x ^ par;
                            if (!__any_sync(0xffffffffu, bad & 1)) break;
                            const uint2* ps = reinterpret_cast<const uint2*>(
                                g_part + ((m * 9 + c) * 8 + f) * (8 * 4 * 32) + (warp >> 1) * 32 + lane) + (warp & 1);
#pragma unroll
                            for (int q = 0; q < 8; q++) {
                                unsigned long long w;
                                asm volatile("ld.relaxed.gpu.global.b64 %0, [%1];" : "=l"(w) : "l"(ps + q * 256) : "memory");
                                v[k][q] = make_uint2((uint32_t)w, (uint32_t)(w >> 32));
                            }
                            if (++tries > (1 << 20)) asm volatile("trap;");
                        }
                        const uint32_t sx = hadd2_bf(hadd2_bf(hadd2_bf(v[k][0].x, v[k][1].x), hadd2_bf(v[k][2].x, v[k][3].x)),
                                                     hadd2_bf(hadd2_bf(v[k][4].x, v[k][5].x), hadd2_bf(v[k][6].x, v[k][7].x)));
                        const uint32_t sy = hadd2_bf(hadd2_bf(hadd2_bf(v[k][0].y, v[k][1].y), hadd2_bf(v[k][2].y, v[k][3].y)),
                                                     hadd2_bf(hadd2_bf(v[k][4].y, v[k][5].y), hadd2_bf(v[k][6].y, v[k][7].y)));
                        o32[c * 32] = hadd2_bf(hmul2_bf(gA, av[k].x), hmul2_bf(oA, hfma2_bf(sx, half2, bb[k])));
                        o32[c * 32 + 4 * D_MODEL] = hadd2_bf(hmul2_bf(gB, av[k].y), hmul2_bf(oB, hfma2_bf(sy, half2, bb[k])));
                    }
                }
                if (warp == 0) DBG(32 + grp);
            }
        }
        asm volatile("barrier.cluster.arrive.release.aligned;\nbarrier.cluster.wait.acquire.aligned;" ::: "memory");
        if (warp == 0) DBG(13);
    }
}

typedef CUresult (*EncodeFn)(CUtensorMap*, CUtensorMapDataType, cuuint32_t, void*, const cuuint64_t*,
                             const cuuint64_t*, const cuuint32_t*, const cuuint32_t*, CUtensorMapInterleave,
                             CUtensorMapSwizzle, CUtensorMapL2promotion, CUtensorMapFloatOOBfill);

static void make_map(EncodeFn enc, CUtensorMap* m, const void* ptr, uint64_t cols, uint64_t rows, uint32_t box_c,
                     uint32_t box_r, CUtensorMapSwizzle swz = CU_TENSOR_MAP_SWIZZLE_128B) {
    cuuint64_t dim[2] = {cols, rows};
    cuuint64_t str[1] = {cols * 2};
    cuuint32_t box[2] = {box_c, box_r};
    cuuint32_t es[2] = {1, 1};
    enc(m, CU_TENSOR_MAP_DATA_TYPE_BFLOAT16, 2, const_cast<void*>(ptr), dim, str, box, es,
        CU_TENSOR_MAP_INTERLEAVE_NONE, swz, CU_TENSOR_MAP_L2_PROMOTION_L2_128B,
        CU_TENSOR_MAP_FLOAT_OOB_FILL_NONE);
}

}

extern "C" void kernel_launch(void* const* d_in, const int* in_sizes, int n_in, void* d_out, int out_size) {
    const bf16* u = (const bf16*)d_in[0];
    const bf16* A_re = (const bf16*)d_in[1];
    const bf16* A_im = (const bf16*)d_in[2];
    const bf16* B_re = (const bf16*)d_in[3];
    const bf16* B_im = (const bf16*)d_in[4];
    const bf16* C_re = (const bf16*)d_in[5];
    const bf16* C_im = (const bf16*)d_in[6];
    const bf16* log_dt = (const bf16*)d_in[7];
    const bf16* Dskip = (const bf16*)d_in[8];
    const bf16* w1 = (const bf16*)d_in[10];
    const bf16* b1 = (const bf16*)d_in[11];
    const bf16* w2 = (const bf16*)d_in[12];
    const bf16* b2 = (const bf16*)d_in[13];
    const bf16* gw = (const bf16*)d_in[14];
    bf16* out = (bf16*)d_out;

    static EncodeFn enc = nullptr;
    if (!enc) {
        void* fn = nullptr;
        cudaDriverEntryPointQueryResult q;
        cudaGetDriverEntryPoint("cuTensorMapEncodeTiled", &fn, cudaEnableDefault, &q);
        enc = (EncodeFn)fn;
        cudaFuncSetAttribute(mlp_kernel, cudaFuncAttributeMaxDynamicSharedMemorySize, MLP_SMEM);
        cudaFuncSetAttribute(ssm::ssm_kernel, cudaFuncAttributeMaxDynamicSharedMemorySize, ssm::K1_SMEM);
    }
    static void* aT_ptr = nullptr;
    if (!aT_ptr) cudaGetSymbolAddress(&aT_ptr, g_aT);
    CUtensorMap tmx, tmw1, tmw2, tma;
    make_map(enc, &tma, aT_ptr, L_SEQ, D_MODEL, 16, 192, CU_TENSOR_MAP_SWIZZLE_NONE);
    make_map(enc, &tmx, u, D_MODEL, L_SEQ, 64, 128);
    make_map(enc, &tmw1, w1, F_DIM, D_MODEL, 64, 48);
    make_map(enc, &tmw2, w2, D_MODEL, F_DIM, 64, 48);

    cudaStream_t st = cudaStreamPerThread;
    ssm::Params sp{A_re, A_im, B_re, B_im, C_re, C_im, log_dt, Dskip};
    CUtensorMap tmc, tmo;
    make_map(enc, &tmc, u, D_MODEL, L_SEQ, 8, 256, CU_TENSOR_MAP_SWIZZLE_NONE);
    make_map(enc, &tmo, aT_ptr, 64, D_MODEL * 32, 64, 32);
    ssm::ssm_kernel<<<ssm::K1_CTAS, 128 * ssm::K1_WGS, ssm::K1_SMEM, st>>>(tmc, tmo, u, gw, sp);
    cudaLaunchConfig_t cfg = {};
    cfg.gridDim = dim3(128);
    cfg.blockDim = dim3(384);
    cfg.dynamicSmemBytes = MLP_SMEM;
    cfg.stream = st;
    cudaLaunchAttribute at[1];
    at[0].id = cudaLaunchAttributeProgrammaticStreamSerialization;
    at[0].val.programmaticStreamSerializationAllowed = 1;
    cfg.attrs = at;
    cfg.numAttrs = 1;
    cudaLaunchKernelEx(&cfg, mlp_kernel, tmx, tmw1, tmw2, tma, b1, b2, out);
}
```

```cpp
#include <cuda_runtime.h>
#include <cuda_bf16.h>
#include <cuda.h>
#include <stdint.h>

namespace {

constexpr int L_SEQ = 2048;
constexpr int D_MODEL = 576;
constexpr int F_DIM = 4608;
constexpr int N_MODES = 128;

typedef __nv_bfloat16 bf16;

__device__ uint2 g_rowstat[L_SEQ];
__device__ float g_gate[L_SEQ];
__device__ bf16 g_aT[D_MODEL * L_SEQ];
__device__ uint4 g_part[16 * 9 * 8 * 8 * 4 * 32];
__device__ unsigned g_stat_epoch[16];
__device__ unsigned g_epoch;

#define DBG(slot)
#define DBG1(slot)

__device__ __forceinline__ uint32_t smem_u32(const void* p) { return (uint32_t)__cvta_generic_to_shared(p); }
__device__ __forceinline__ float bf16r(float x) { return __bfloat162float(__float2bfloat16_rn(x)); }
__device__ __forceinline__ uint32_t pack_bf16(float lo, float hi) {
    uint32_t r;
    asm("cvt.rn.bf16x2.f32 %0, %1, %2;" : "=r"(r) : "f"(hi), "f"(lo));
    return r;
}
__device__ __forceinline__ float bf_lo(uint32_t v) { return __uint_as_float(v << 16); }
__device__ __forceinline__ float bf_hi(uint32_t v) { return __uint_as_float(v & 0xffff0000u); }

__device__ __forceinline__ void mbar_init(uint32_t bar, int cnt) {
    asm volatile("mbarrier.init.shared::cta.b64 [%0], %1;" ::"r"(bar), "r"(cnt));
}
__device__ __forceinline__ void mbar_expect(uint32_t bar, int bytes) {
    asm volatile("mbarrier.arrive.expect_tx.shared::cta.b64 _, [%0], %1;" ::"r"(bar), "r"(bytes) : "memory");
}
__device__ __forceinline__ void mbar_arrive_cluster(uint32_t bar, uint32_t cta) {
    asm volatile(
        "{\n.reg .b32 ra;\nmapa.shared::cluster.u32 ra, %0, %1;\n"
        "mbarrier.arrive.shared::cluster.b64 _, [ra];\n}\n" ::"r"(bar), "r"(cta) : "memory");
}
__device__ __forceinline__ bool mbar_try(uint32_t bar, int parity) {
    uint32_t ok;
    asm volatile(
        "{\n.reg .pred p;\nmbarrier.try_wait.parity.shared::cta.b64 p, [%1], %2;\nselp.u32 %0, 1, 0, p;\n}\n"
        : "=r"(ok) : "r"(bar), "r"(parity) : "memory");
    return ok != 0;
}
__device__ __forceinline__ void mbar_wait(uint32_t bar, int parity) {
    asm volatile(
        "{\n.reg .pred p;\n.reg .u32 n;\nmov.u32 n, 0;\n"
        "WAIT_LOOP:\n"
        "mbarrier.try_wait.parity.shared::cta.b64 p, [%0], %1;\n"
        "@p bra WAIT_DONE;\n"
        "add.u32 n, n, 1;\n"
        "setp.lt.u32 p, n, 4194304;\n"
        "@p bra WAIT_LOOP;\n"
        "trap;\n"
        "WAIT_DONE:\n}\n" ::"r"(bar), "r"(parity) : "memory");
}
__device__ __forceinline__ void tma2d(uint32_t dst, const CUtensorMap* m, int c0, int c1, uint32_t bar) {
    asm volatile(
        "cp.async.bulk.tensor.2d.shared::cluster.global.mbarrier::complete_tx::bytes [%0], [%1, {%3,%4}], [%2];"
        ::"r"(dst), "l"(m), "r"(bar), "r"(c0), "r"(c1) : "memory");
}
__device__ __forceinline__ void tma2d_mc(uint32_t dst, const CUtensorMap* m, int c0, int c1, uint32_t bar,
                                         uint16_t mask) {
    asm volatile(
        "cp.async.bulk.tensor.2d.shared::cluster.global.mbarrier::complete_tx::bytes.multicast::cluster.L2::cache_hint "
        "[%0], [%1, {%3,%4}], [%2], %5, %6;"
        ::"r"(dst), "l"(m), "r"(bar), "r"(c0), "r"(c1), "h"(mask), "l"(0x12F0000000000000ull) : "memory");
}
__device__ __forceinline__ void ldsm_x4(uint32_t (&r)[4], uint32_t addr) {
    asm volatile("ldmatrix.sync.aligned.m8n8.x4.shared.b16 {%0,%1,%2,%3}, [%4];"
                 : "=r"(r[0]), "=r"(r[1]), "=r"(r[2]), "=r"(r[3]) : "r"(addr) : "memory");
}
#define WG_FENCE() asm volatile("wgmma.fence.sync.aligned;\n" ::: "memory")
#define WG_COMMIT() asm volatile("wgmma.commit_group.sync.aligned;\n" ::: "memory")
#define WG_WAIT(n) asm volatile("wgmma.wait_group.sync.aligned %0;\n" ::"n"(n) : "memory")

template <int SCALE_D, int OFF>
__device__ __forceinline__ void wgmma_rs_n64(float (&d)[32], const uint32_t (&a)[4], uint32_t desc_lo) {
    asm volatile(
        "{\n.reg .pred p;\n.reg .b32 lo;\n.reg .b64 dsc;\nsetp.ne.b32 p, %37, 0;\n"
        "add.u32 lo, %36, %38;\nmov.b64 dsc, {lo, 0x40000040};\n"
        "wgmma.mma_async.sync.aligned.m64n64k16.f32.bf16.bf16 "
        "{%0,%1,%2,%3,%4,%5,%6,%7,%8,%9,%10,%11,%12,%13,%14,%15,%16,%17,%18,%19,%20,%21,%22,%23,%24,%25,%26,%27,%28,%29,%30,%31},"
        "{%32,%33,%34,%35}, dsc, p, 1, 1, 1;\n}\n"
        : "+f"(d[0]), "+f"(d[1]), "+f"(d[2]), "+f"(d[3]), "+f"(d[4]), "+f"(d[5]), "+f"(d[6]), "+f"(d[7]),
          "+f"(d[8]), "+f"(d[9]), "+f"(d[10]), "+f"(d[11]), "+f"(d[12]), "+f"(d[13]), "+f"(d[14]), "+f"(d[15]),
          "+f"(d[16]), "+f"(d[17]), "+f"(d[18]), "+f"(d[19]), "+f"(d[20]), "+f"(d[21]), "+f"(d[22]), "+f"(d[23]),
          "+f"(d[24]), "+f"(d[25]), "+f"(d[26]), "+f"(d[27]), "+f"(d[28]), "+f"(d[29]), "+f"(d[30]), "+f"(d[31])
        : "r"(a[0]), "r"(a[1]), "r"(a[2]), "r"(a[3]), "r"(desc_lo), "n"(SCALE_D), "n"(OFF));
}
template <int OFF, int AOFF>
__device__ __forceinline__ void wgmma_ss_n64(float (&d)[32], uint32_t adesc_lo, uint32_t desc_lo) {
    asm volatile(
        "{\n.reg .pred p;\n.reg .b32 lo;\n.reg .b64 dsc, dsa;\nsetp.ne.b32 p, 1, 0;\n"
        "add.u32 lo, %33, %34;\nmov.b64 dsc, {lo, 0x40000040};\n"
        "add.u32 lo, %32, %35;\nmov.b64 dsa, {lo, 0x40000040};\n"
        "wgmma.mma_async.sync.aligned.m64n64k16.f32.bf16.bf16 "
        "{%0,%1,%2,%3,%4,%5,%6,%7,%8,%9,%10,%11,%12,%13,%14,%15,%16,%17,%18,%19,%20,%21,%22,%23,%24,%25,%26,%27,%28,%29,%30,%31},"
        "dsa, dsc, p, 1, 1, 0, 1;\n}\n"
        : "+f"(d[0]), "+f"(d[1]), "+f"(d[2]), "+f"(d[3]), "+f"(d[4]), "+f"(d[5]), "+f"(d[6]), "+f"(d[7]),
          "+f"(d[8]), "+f"(d[9]), "+f"(d[10]), "+f"(d[11]), "+f"(d[12]), "+f"(d[13]), "+f"(d[14]), "+f"(d[15]),
          "+f"(d[16]), "+f"(d[17]), "+f"(d[18]), "+f"(d[19]), "+f"(d[20]), "+f"(d[21]), "+f"(d[22]), "+f"(d[23]),
          "+f"(d[24]), "+f"(d[25]), "+f"(d[26]), "+f"(d[27]), "+f"(d[28]), "+f"(d[29]), "+f"(d[30]), "+f"(d[31])
        : "r"(adesc_lo), "r"(desc_lo), "n"(OFF), "n"(AOFF));
}
constexpr int NAF = 34;
template <int S, int FIRST>
__device__ __forceinline__ void mma_stage(float (&d)[32], const uint32_t (&af)[NAF][4], uint32_t desc_lo,
                                          uint32_t adesc_lo) {
    constexpr int B = (S * 96 * 128) >> 4;
    wgmma_rs_n64<FIRST ? 0 : 1, B + 0 * 128>(d, af[S * 6 + 0], desc_lo);
    wgmma_rs_n64<1, B + 1 * 128>(d, af[S * 6 + 1], desc_lo);
    wgmma_rs_n64<1, B + 2 * 128>(d, af[S * 6 + 2], desc_lo);
    wgmma_rs_n64<1, B + 3 * 128>(d, af[S * 6 + 3], desc_lo);
    if constexpr (S < 5) {
        wgmma_rs_n64<1, B + 4 * 128>(d, af[S * 6 + 4], desc_lo);
        wgmma_rs_n64<1, B + 5 * 128>(d, af[S * 6 + 5], desc_lo);
    } else {
        wgmma_ss_n64<B + 4 * 128, 4>(d, adesc_lo, desc_lo);
        wgmma_ss_n64<B + 5 * 128, 6>(d, adesc_lo, desc_lo);
    }
}
__device__ __forceinline__ void mma_stage_rt(int s, float (&d)[32], const uint32_t (&af)[NAF][4], uint32_t desc_lo,
                                             uint32_t adesc_lo) {
    if (s == 0) mma_stage<0, 1>(d, af, desc_lo, adesc_lo);
    if (s == 1) mma_stage<1, 0>(d, af, desc_lo, adesc_lo);
    if (s == 2) mma_stage<2, 0>(d, af, desc_lo, adesc_lo);
    if (s == 3) mma_stage<3, 0>(d, af, desc_lo, adesc_lo);
    if (s == 4) mma_stage<4, 0>(d, af, desc_lo, adesc_lo);
    if (s == 5) mma_stage<5, 0>(d, af, desc_lo, adesc_lo);
}
__device__ __forceinline__ void stsm_x4(const uint32_t (&r)[4], uint32_t addr) {
    asm volatile("stmatrix.sync.aligned.m8n8.x4.shared.b16 [%4], {%0,%1,%2,%3};"
                 ::"r"(r[0]), "r"(r[1]), "r"(r[2]), "r"(r[3]), "r"(addr) : "memory");
}
__device__ __forceinline__ void fence_acc(float (&d)[32]) {
#pragma unroll
    for (int i = 0; i < 32; i++) asm volatile("" : "+f"(d[i])::"memory");
}

__device__ __forceinline__ float gelu_tanh(float x) {
    const float k0 = 0.7978845608028654f, k1 = 0.7978845608028654f * 0.044715f;
    float u = x * fmaf(x * x, k1, k0);
    float th;
    asm("tanh.approx.f32 %0, %1;" : "=f"(th) : "f"(u));
    float hx = 0.5f * x;
    return fmaf(hx, th, hx);
}

__device__ __forceinline__ uint32_t hadd2_bf(uint32_t a, uint32_t b) {
    uint32_t r;
    asm("add.rn.bf16x2 %0, %1, %2;" : "=r"(r) : "r"(a), "r"(b));
    return r;
}
__device__ __forceinline__ uint32_t hsub2_bf(uint32_t a, uint32_t b) {
    uint32_t r;
    asm("sub.rn.bf16x2 %0, %1, %2;" : "=r"(r) : "r"(a), "r"(b));
    return r;
}
__device__ __forceinline__ uint32_t hmul2_bf(uint32_t a, uint32_t b) {
    uint32_t r;
    asm("mul.rn.bf16x2 %0, %1, %2;" : "=r"(r) : "r"(a), "r"(b));
    return r;
}
__device__ __forceinline__ uint32_t hfma2_bf(uint32_t a, uint32_t b, uint32_t c) {
    uint32_t r;
    asm("fma.rn.bf16x2 %0, %1, %2, %3;" : "=r"(r) : "r"(a), "r"(b), "r"(c));
    return r;
}
namespace ssm {
constexpr int O_H = 0;
constexpr int O_L = 12288;
constexpr int HL_END = O_L + 16384;
constexpr int O_Q = 0;
constexpr int O_Q12 = 5120;
constexpr int O_Q34 = O_Q12 + 1280;
constexpr int O_Y12 = O_Q34 + 2048 - 2176;
constexpr int O_Y34 = O_Y12 + 8704 - 4352;
constexpr int O_W3 = O_Y34 + 8704 + 256;
constexpr int O_W4 = O_W3 + 2048 + 256;
constexpr int O_W5 = O_W4 + 2048;
constexpr int O_U = HL_END;
constexpr int O_RAW = O_U + 6144;
constexpr int O_W1 = O_U + 6144 + 256;
constexpr int O_W2 = O_W1 + 3072 + 256;
constexpr int O_ST = O_RAW;
constexpr int O_KN = O_W2 + 3072;
constexpr int O_A12 = O_KN + 1344;
constexpr int O_A3 = O_A12 + 384;
constexpr int O_KQ = O_A3 + 304;
constexpr int WG_BYTES = 44032;
static_assert(O_W5 + 2048 <= HL_END && O_KQ + 16 <= WG_BYTES && WG_BYTES % 1024 == 0 && O_RAW + 8192 <= WG_BYTES, "map");

struct cplx { float r, i; };
__device__ __forceinline__ cplx cmul(cplx a, cplx b) {
    cplx o;
    o.r = fmaf(a.r, b.r, -a.i * b.i);
    o.i = fmaf(a.r, b.i, a.i * b.r);
    return o;
}
__device__ __forceinline__ cplx cexp_l(float lr, float li, float l) {
    const float e = exp2f((lr * l) * 1.4426950408889634f);
    const float ang = li * l;
    const float k = rintf(ang * 0.15915494309189535f);
    float r = fmaf(k, -6.2831854820251465f, ang);
    r = fmaf(k, 1.7484556000744487e-07f, r);
    cplx o;
    o.r = e * __cosf(r);
    o.i = e * __sinf(r);
    return o;
}
template <typename T> __device__ __forceinline__ T* sp(uint32_t a) {
    return reinterpret_cast<T*>(__cvta_shared_to_generic(a));
}
__device__ __forceinline__ void sts32(uint32_t a, uint32_t v) { *sp<uint32_t>(a) = v; }
__device__ __forceinline__ void sts16(uint32_t a, uint32_t v) { *sp<unsigned short>(a) = (unsigned short)v; }
__device__ __forceinline__ uint32_t lds16(uint32_t a) { return *sp<unsigned short>(a); }
__device__ __forceinline__ uint32_t lds32(uint32_t a) { return *sp<uint32_t>(a); }
__device__ __forceinline__ float ldsf(uint32_t a) { return *sp<float>(a); }
__device__ __forceinline__ uint2 lds64(uint32_t a) { return *sp<uint2>(a); }
__device__ __forceinline__ void sts64(uint32_t a, uint32_t x, uint32_t y) { *sp<uint2>(a) = make_uint2(x, y); }
__device__ __forceinline__ void sts64f(uint32_t a, float x, float y) { *sp<float2>(a) = make_float2(x, y); }
__device__ __forceinline__ void sts128(uint32_t a, uint32_t x, uint32_t y, uint32_t z, uint32_t w) {
    *sp<uint4>(a) = make_uint4(x, y, z, w);
}
__device__ __forceinline__ uint4 lds128(uint32_t a) { return *sp<uint4>(a); }
__device__ __forceinline__ void wg_bar(int id) { asm volatile("bar.sync %0, 128;" ::"r"(id) : "memory"); }
__device__ __forceinline__ uint32_t u_addr(uint32_t sb, int grp) {
    const int gq = grp + 128;
    return sb + O_U + (gq >> 3) * 128 + (((gq ^ (gq >> 3)) & 7) << 4);
}
template <int SCALE_D, int OA, int OB>
__device__ __forceinline__ void wgmma_ss_n32(float (&d)[16], uint32_t dl) {
    asm volatile(
        "{\n.reg .pred p;\n.reg .b32 lo;\n.reg .b64 x, y;\nsetp.ne.b32 p, %17, 0;\n"
        "add.u32 lo, %16, %18;\nmov.b64 x, {lo, 0x40000040};\nadd.u32 lo, %16, %19;\nmov.b64 y, {lo, 0x40000040};\n"
        "wgmma.mma_async.sync.aligned.m64n32k16.f32.bf16.bf16 "
        "{%0,%1,%2,%3,%4,%5,%6,%7,%8,%9,%10,%11,%12,%13,%14,%15}, x, y, p, 1, 1, 0, 0;\n}\n"
        : "+f"(d[0]), "+f"(d[1]), "+f"(d[2]), "+f"(d[3]), "+f"(d[4]), "+f"(d[5]), "+f"(d[6]), "+f"(d[7]),
          "+f"(d[8]), "+f"(d[9]), "+f"(d[10]), "+f"(d[11]), "+f"(d[12]), "+f"(d[13]), "+f"(d[14]), "+f"(d[15])
        : "r"(dl), "n"(SCALE_D), "n"(OA), "n"(OB));
}
template <int OB>
__device__ __forceinline__ void wgmma_rs_n32(float (&d)[16], uint32_t a0, uint32_t a1, uint32_t a2, uint32_t a3,
                                             uint32_t dl) {
    asm volatile(
        "{\n.reg .pred p;\n.reg .b32 lo;\n.reg .b64 y;\nsetp.ne.b32 p, 1, 0;\n"
        "add.u32 lo, %20, %21;\nmov.b64 y, {lo, 0x40000040};\n"
        "wgmma.mma_async.sync.aligned.m64n32k16.f32.bf16.bf16 "
        "{%0,%1,%2,%3,%4,%5,%6,%7,%8,%9,%10,%11,%12,%13,%14,%15}, {%16,%17,%18,%19}, y, p, 1, 1, 0;\n}\n"
        : "+f"(d[0]), "+f"(d[1]), "+f"(d[2]), "+f"(d[3]), "+f"(d[4]), "+f"(d[5]), "+f"(d[6]), "+f"(d[7]),
          "+f"(d[8]), "+f"(d[9]), "+f"(d[10]), "+f"(d[11]), "+f"(d[12]), "+f"(d[13]), "+f"(d[14]), "+f"(d[15])
        : "r"(a0), "r"(a1), "r"(a2), "r"(a3), "r"(dl), "n"(OB));
}
template <int KS> struct KgenSteps {
    static __device__ __forceinline__ void run(float (&d)[16], uint32_t dl) {
        KgenSteps<KS - 1>::run(d, dl);
        constexpr int k = KS - 1;
        wgmma_ss_n32<(k > 0), (O_H + (k / 4) * 3072 + (k % 4) * 32) / 16, (O_L + (k / 4) * 4096 + (k % 4) * 32) / 16>(d, dl);
    }
};
template <> struct KgenSteps<0> { static __device__ __forceinline__ void run(float (&)[16], uint32_t) {} };
template <int K0, int N, int I> struct NearSteps {
    static __device__ __forceinline__ void run(float (&d)[16], const uint4 (&f)[N], uint32_t dl) {
        NearSteps<K0, N, I - 1>::run(d, f, dl);
        constexpr int k = K0 + I - 1, dd = k / 4, kk = 4 * dd - (k - 3);
        wgmma_rs_n32<(O_U + (16 - dd) * 128 + kk * 32) / 16>(d, f[I - 1].x, f[I - 1].y, f[I - 1].z, f[I - 1].w, dl);
    }
};
template <int K0, int N> struct NearSteps<K0, N, 0> {
    static __device__ __forceinline__ void run(float (&)[16], const uint4 (&)[N], uint32_t) {}
};
template <int N>
__device__ __forceinline__ void load_toep(uint4 (&f)[N], uint32_t addr, uint32_t& prev) {
#pragma unroll
    for (int k = 0; k < N; k++)
    { const uint2 v = lds64(addr + k * 128); f[k].x = v.x; f[k].y = v.y; }
#pragma unroll
    for (int k = 0; k < N; k++) {
        f[k].z = prev;
        f[k].w = f[k].x;
        prev = f[k].y;
    }
}
__device__ __forceinline__ void mma16816(float (&d)[4], uint32_t a0, uint32_t a1, uint32_t a2, uint32_t b0,
                                         uint32_t b1) {
    asm("mma.sync.aligned.m16n8k16.row.col.f32.bf16.bf16.f32 {%0,%1,%2,%3}, {%4,%5,%6,%4}, {%7,%8}, {%0,%1,%2,%3};"
                 : "+f"(d[0]), "+f"(d[1]), "+f"(d[2]), "+f"(d[3])
                 : "r"(a0), "r"(a1), "r"(a2), "r"(b0), "r"(b1));
}
__device__ __forceinline__ uint4 ldsm_x4_t(uint32_t addr) {
    uint4 r;
    asm volatile("ldmatrix.sync.aligned.m8n8.x4.trans.shared.b16 {%0,%1,%2,%3}, [%4];"
                 : "=r"(r.x), "=r"(r.y), "=r"(r.z), "=r"(r.w) : "r"(addr));
    return r;
}
__device__ __forceinline__ int kc_index(int x) {
    const int i2 = 128 + ((x + ((x >> 1) & 1)) >> 1), i4 = 256 + ((x + 1 + ((x >> 2) & 1)) >> 2);
    return x < 256 ? x : (x < 512 ? i2 : i4);
}

struct Params { const bf16 *A_re, *A_im, *B_re, *B_im, *C_re, *C_im, *log_dt, *Dskip; };
struct ModeIn { float ar, ai, br, bi, cr, ci, ldt, dsk; };
__device__ __forceinline__ ModeIn load_mode(const Params& p, int d, int n) {
    ModeIn m;
    const int i = d * N_MODES + n;
    m.ar = __bfloat162float(p.A_re[i]); m.ai = __bfloat162float(p.A_im[i]);
    m.br = __bfloat162float(p.B_re[i]); m.bi = __bfloat162float(p.B_im[i]);
    m.cr = __bfloat162float(p.C_re[i]); m.ci = __bfloat162float(p.C_im[i]);
    m.ldt = __bfloat162float(p.log_dt[d]); m.dsk = __bfloat162float(p.Dskip[d]);
    return m;
}

__device__ __forceinline__ void gen_powers(const ModeIn& mi, uint32_t sb, int t) {
    const float dt = bf16r(expf(mi.ldt));
    const float lr = dt * mi.ar, li = dt * mi.ai;
    const float br = dt * mi.br, bi = dt * mi.bi;
    cplx c;
    c.r = mi.cr * br - mi.ci * bi;
    c.i = mi.cr * bi + mi.ci * br;
    const cplx z = cexp_l(lr, li, 1.f), wv = cexp_l(lr, li, 8.f), Z = cexp_l(lr, li, 256.f);
    const cplx z2 = cmul(z, z), z4 = cmul(z2, z2);
    const uint32_t x0 = ((t & 31) >> 2) * 16 + (t & 3) * 4;
    uint32_t xs[8];
#pragma unroll
    for (int j = 0; j < 8; j++) xs[j] = sb + (x0 ^ (j << 4));
    const uint32_t ho = O_H + (t >> 5) * 3072, lo_ = O_L + (t >> 5) * 4096;
#define PUT_H(row, v) sts32(xs[(row) & 7] + ho + (row) * 128, pack_bf16((v).r, -(v).i))
#define PUT_L(row, v) sts32(xs[(row) & 7] + lo_ + (row) * 128, pack_bf16((v).r, (v).i))
    cplx h = c;
    PUT_H(0, h);
#pragma unroll
    for (int k = 1; k < 8; k++) { h = cmul(h, z); PUT_H(k, h); }
    cplx hz = cmul(c, Z);
    PUT_H(8, hz);
    { cplx a = cmul(hz, z2); PUT_H(9, a); a = cmul(hz, z4); PUT_H(10, a); a = cmul(a, z2); PUT_H(11, a); }
    hz = cmul(hz, Z); PUT_H(12, hz);
    { cplx a = cmul(hz, z4); PUT_H(13, a); }
    hz = cmul(hz, Z); PUT_H(14, hz);
    { cplx a = cmul(hz, z4); PUT_H(15, a); }
#pragma unroll
    for (int k = 16; k < 21; k++) { hz = cmul(hz, Z); PUT_H(k, hz); }
    const cplx w2 = cmul(wv, wv);
    cplx le, lo = wv;
    le.r = 1.f; le.i = 0.f;
    uint32_t lb = lo_;
#pragma unroll 1
    for (int kb = 0; kb < 4; kb++) {
#pragma unroll
        for (int k = 0; k < 8; k += 2) {
            sts32(xs[k] + lb + k * 128, pack_bf16(le.r, le.i));
            sts32(xs[k + 1] + lb + (k + 1) * 128, pack_bf16(lo.r, lo.i));
            le = cmul(le, w2); lo = cmul(lo, w2);
        }
        lb += 1024;
    }
}

__device__ __forceinline__ uint4 pack8(const float (&v)[8]) {
    return make_uint4(pack_bf16(v[0], v[1]), pack_bf16(v[2], v[3]), pack_bf16(v[4], v[5]), pack_bf16(v[6], v[7]));
}
__device__ __forceinline__ void st16B(uint32_t a, const uint4& v) { *sp<uint4>(a) = v; }

__device__ __forceinline__ void build_windows(uint32_t sb, int t) {
    if (t < 64) {
        const int which = t >> 4;
        sts128(sb + (which == 0 ? O_W1 : which == 1 ? O_W2 : which == 2 ? O_W3 : O_W4) - 256 + (t & 15) * 16, 0, 0, 0, 0);
    }
#pragma unroll
    for (int r = 0; r < 2; r++) {
        const int grp = t + r * 128;
        if (grp < 192) {
            const uint4 c0 = lds128(u_addr(sb, grp - 2)), c1 = lds128(u_addr(sb, grp - 1)), c2 = lds128(u_addr(sb, grp));
            float v[24];
            const uint32_t ww[12] = {c0.x, c0.y, c0.z, c0.w, c1.x, c1.y, c1.z, c1.w, c2.x, c2.y, c2.z, c2.w};
#pragma unroll
            for (int i = 2; i < 11; i++) { v[2 * i] = bf_lo(ww[i]); v[2 * i + 1] = bf_hi(ww[i]); }
            float p2[15];
#pragma unroll
            for (int j = 0; j < 15; j++) p2[j] = v[5 + j] + v[6 + j];
            float b1[8], b2[8];
#pragma unroll
            for (int i = 0; i < 8; i++) {
                b2[i] = p2[i + 6] + v[13 + i];
                b1[i] = p2[i + 1] + p2[i + 3] + v[10 + i];
            }
            st16B(sb + O_W1 + grp * 16, pack8(b1));
            st16B(sb + O_W2 + grp * 16, pack8(b2));
            if (r == 0) {
                float b3[8], b5[8];
#pragma unroll
                for (int i = 0; i < 8; i++) {
                    b3[i] = b1[i] + v[11 + i] + v[5 + i];
                    b5[i] = p2[i + 7];
                }
                st16B(sb + O_W3 + grp * 16, pack8(b3));
                st16B(sb + O_W5 + grp * 16, pack8(b5));
                st16B(sb + O_W4 + grp * 16, make_uint4(hadd2_bf(ww[6], ww[2]), hadd2_bf(ww[7], ww[3]),
                                                       hadd2_bf(ww[8], ww[4]), hadd2_bf(ww[9], ww[5])));
            }
        }
    }
}

__device__ __forceinline__ void build_tables(float (&kd)[16], float dskip, uint32_t sb, int t, int bar) {
    const int lane = t & 31, w = t >> 5, g = lane >> 2, tq = lane & 3;
    if (w == 0) {
        if (lane == 0) kd[0] += dskip;
        const uint32_t kn = sb + O_KN + 128;
#pragma unroll
        for (int j = 0; j < 4; j++) {
            const int lo = 8 * j + 2 * tq;
            const uint32_t p0 = pack_bf16(kd[4 * j], kd[4 * j + 1]), p1 = pack_bf16(kd[4 * j + 2], kd[4 * j + 3]);
            sts16(kn + (g + 8 * lo) * 2, p0);
            sts16(kn + (g + 8 * lo + 8) * 2, p0 >> 16);
            if (g < 4) {
#pragma unroll
                for (int e = 0; e < 2; e++) {
                    const uint32_t val = e ? (p1 >> 16) : p1, ad = kn + (256 + 2 * g + 8 * (lo + e)) * 2;
                    sts16(ad, val);
                    if (!(g & 1)) {
                        sts16(ad + 2, val);
                        if (g + lo + e > 0) sts16(ad - 2, val);
                    }
                }
            } else {
#pragma unroll
                for (int e = 0; e < 2; e++) {
                    const uint32_t val = e ? (p1 >> 16) : p1;
                    const int i8 = 64 + (g >= 6 ? 32 : 0) + lo + e;
                    if (j > 0 || i8 >= 66) {
                        sts16(sb + O_A12 + (i8 - 48) * 4 - ((g & 1) ? 0 : 2), val);
                    } else if (g & 1) {
                        sts16(kn + (8 * i8 + 3) * 2, val); sts16(kn + (8 * i8 + 4) * 2, val); sts16(kn + (8 * i8 + 5) * 2, val);
                    } else {
#pragma unroll
                        for (int dd = -2; dd <= 2; dd++)
                            if (i8 == 65 || dd >= -1) sts16(kn + (8 * i8 + dd) * 2, val);
                    }
                }
            }
        }
    } else if (w == 1) {
        if (g < 4) {
#pragma unroll
            for (int j = 0; j < 4; j++) {
                const int i8 = 128 + 32 * g + 8 * j + 2 * tq;
                const uint32_t p0 = pack_bf16(kd[4 * j], kd[4 * j + 1]);
                if (i8 == 128) { sts16(sb + O_A12 + (127 - 48) * 4 + 2, p0); sts16(sb + O_KQ, p0); }
                else sts16(sb + O_A3 + (i8 - 1 - 112) * 2, p0);
                sts16(sb + O_A3 + (i8 - 112) * 2, p0 >> 16);
            }
        } else if (lane == 16) {
            sts16(sb + O_A3 + (255 - 112) * 2, pack_bf16(kd[0], 0.f));
        }
    }
    wg_bar(bar);
    DBG1(4);
    {
#pragma unroll
        for (int r = 0; r < 2; r++) {
            const int i = t + r * 128;
            if (i < 160) {
                const uint32_t ka = sb + O_KN + (4 * i + 8) * 2;
                const uint32_t wm = lds32(ka - 4), w3 = lds32(ka + 12);
                const uint2 wa = lds64(ka), wb = lds64(ka + 16);
                const uint32_t w0 = wa.x, w1 = wa.y, w4 = wb.x, w5 = wb.y;
                sts128(sb + O_Q + i * 32, __byte_perm(w0, wm, 0x7610), __byte_perm(w4, w3, 0x7610),
                       __byte_perm(w0, w0, 0x1032), __byte_perm(w4, w4, 0x1032));
                sts128(sb + O_Q + i * 32 + 16, __byte_perm(w1, w0, 0x7610), __byte_perm(w5, w4, 0x7610),
                       __byte_perm(w1, w1, 0x1032), __byte_perm(w5, w5, 0x1032));
            }
        }
        {
            const uint32_t aa = sb + O_A3 + (8 + t) * 2;
            const uint32_t p0 = lds16(aa) | (lds16(aa - 2) << 16), p1 = lds16(aa + 16) | (lds16(aa + 14) << 16);
            const uint32_t msk = (t & 1) ? 0x0000ffffu : 0xffff0000u;
            sts128(sb + O_Q34 + t * 16, p0, p1, p0 & msk, p1 & msk);
        }
        if (t >= 48) {
            const uint32_t aa = sb + O_A12 + (t - 48 + 8) * 4;
            const uint32_t e0 = lds32(aa), e1 = lds32(aa - 4), f0 = lds32(aa + 32), f1 = lds32(aa + 28);
            sts128(sb + O_Q12 + (t - 48) * 16, __byte_perm(e0, e1, 0x7632), __byte_perm(f0, f1, 0x7632),
                   __byte_perm(e0, e1, 0x5410), __byte_perm(f0, f1, 0x5410));
        }
    }
}

__device__ __forceinline__ void convolve(int d, uint32_t sb, int t, int bar, const CUtensorMap* tmo) {
    const int lane = t & 31, w = t >> 5, g = lane >> 2, tq = lane & 3;
    const uint32_t dl = (sb & 0x3FFFF) >> 4;
    float y[16];
#pragma unroll
    for (int i = 0; i < 16; i++) y[i] = 0.f;
    {
        const uint32_t qa = sb + O_Q + (16 * w + g - 2 * tq + 56 - 48) * 8;
        uint32_t prev = 0;
        uint32_t qp = qa, du = dl;
#pragma unroll 1
        for (int jj = 0; jj < 4; jj++) {
            uint4 F[8];
            load_toep<8>(F, qp, prev);
            WG_FENCE();
            NearSteps<0, 8, 8>::run(y, F, du);
            WG_COMMIT();
            WG_WAIT(0);
            qp += 8 * 128;
            du -= 16;
        }
        uint4 FC[5];
        load_toep<5>(FC, qp, prev);
        WG_FENCE();
        NearSteps<0, 5, 5>::run(y, FC, du);
        WG_COMMIT();
        WG_WAIT(0);
#pragma unroll
        for (int i = 0; i < 16; i++) asm volatile("" : "+f"(y[i])::"memory");
    }
    DBG1(6);
    {
        const int par = w & 1;
        const uint32_t qoff = sb + (g - 2 * tq) * 16;
        const uint32_t roff = sb + (lane & 15) * 16 + par * 256;
        const uint32_t yoff = sb + (136 * par + 8 * g + 2 * tq) * 4;
        if (w < 2) {
            const uint32_t wb = roff + ((lane >> 4) ? O_W2 : O_W1);
            uint4 f[5];
#pragma unroll
            for (int q = 4; q <= 8; q++) f[q - 4] = lds128(qoff + O_Q12 + (16 * q - 56) * 16);
            uint4 bt[12];
#pragma unroll
            for (int i = 0; i < 6; i++) {
                if (i == 0) bt[0] = ldsm_x4_t(wb - 256);
                bt[2 * i + 1] = ldsm_x4_t(wb + (2 * i) * 256);
                if (i > 0) bt[2 * i] = ldsm_x4_t(wb + (2 * i - 1) * 256);
                float a0[4] = {0.f, 0.f, 0.f, 0.f}, a1[4] = {0.f, 0.f, 0.f, 0.f};
#pragma unroll
                for (int q = 4; q <= 8; q++) {
                    const int k = 2 * i + 4 - q;
                    if (k >= -1) {
                        mma16816(a0, f[q - 4].x, f[q - 4].y, q > 4 ? f[q > 4 ? q - 5 : 0].y : 0u, bt[k + 1].x, bt[k + 1].y);
                        mma16816(a1, f[q - 4].z, f[q - 4].w, q > 4 ? f[q > 4 ? q - 5 : 0].w : 0u, bt[k + 1].z, bt[k + 1].w);
                    }
                }
                const uint32_t ya = yoff + O_Y12 + 136 * (4 + 2 * i) * 4;
                sts64f(ya, a0[0] + a1[0], a0[1] + a1[1]);
                sts64f(ya + 256, a0[2] + a1[2], a0[3] + a1[3]);
            }
        } else {
            const uint32_t wb = roff + ((lane >> 4) ? O_W4 : O_W3);
            uint4 bt[8];
#pragma unroll
            for (int k = 0; k < 8; k++) bt[k] = ldsm_x4_t(wb + (k - 1) * 256);
            const uint4 b5a = ldsm_x4_t(roff + O_W5 + (lane >> 4) * 512), b5b = ldsm_x4_t(roff + O_W5 + 1024 + (lane >> 4) * 512);
            const uint32_t kq = lds16(sb + O_KQ);
            const uint32_t dg = (g == 2 * tq) ? kq : ((g == 2 * tq + 1) ? (kq << 16) : 0u);
            float acc[4][4];
#pragma unroll
            for (int i = 0; i < 4; i++)
#pragma unroll
                for (int j = 0; j < 4; j++) acc[i][j] = 0.f;
            mma16816(acc[0], dg, 0u, 0u, b5a.x, b5a.y);
            mma16816(acc[1], dg, 0u, 0u, b5a.z, b5a.w);
            mma16816(acc[2], dg, 0u, 0u, b5b.x, b5b.y);
            mma16816(acc[3], dg, 0u, 0u, b5b.z, b5b.w);
            uint32_t pa = 0, pb = 0;
#pragma unroll
            for (int q = 8; q <= 15; q++) {
                const uint4 f = lds128(qoff + O_Q34 + (16 * q - 120) * 16);
#pragma unroll
                for (int i = 0; i < 4; i++) {
                    const int k = 2 * i + 8 - q;
                    if (k >= -1) mma16816(acc[i], f.x, f.y, pa, bt[k + 1].x, bt[k + 1].y);
                }
#pragma unroll
                for (int i = 0; i < 4; i++) {
                    const int k = 2 * i + 8 - q;
                    if (k >= -1) mma16816(acc[i], f.z, f.w, pb, bt[k + 1].z, bt[k + 1].w);
                }
                pa = f.y; pb = f.w;
            }
#pragma unroll
            for (int i = 0; i < 4; i++) {
                const uint32_t ya = yoff + O_Y34 + 136 * (8 + 2 * i) * 4;
                sts64f(ya, acc[i][0], acc[i][1]);
                sts64f(ya + 256, acc[i][2], acc[i][3]);
            }
        }
    }
    wg_bar(bar);
    DBG1(7);
    {
        const uint32_t yb = sb + (136 * tq + 16 * w + g) * 4;
#pragma unroll
        for (int j = 1; j < 4; j++)
#pragma unroll
            for (int e = 0; e < 4; e++) {
                const uint32_t o = yb + (544 * j + 64 * (e & 1) + 8 * (e >> 1)) * 4;
                y[4 * j + e] += ldsf(o + O_Y12);
                if (j >= 2) y[4 * j + e] += ldsf(o + O_Y34);
            }
#pragma unroll
        for (int jp = 0; jp < 2; jp++) {
            const int a = 8 * (2 * jp + (lane >> 4)) + (lane & 7);
            const uint32_t addr = sb + O_ST + a * 128 + (((2 * w + ((lane >> 3) & 1)) ^ (lane & 7)) << 4);
            asm volatile("stmatrix.sync.aligned.m8n8.x4.trans.shared.b16 [%0], {%1,%2,%3,%4};" ::"r"(addr),
                         "r"(pack_bf16(y[8 * jp + 0], y[8 * jp + 1])), "r"(pack_bf16(y[8 * jp + 2], y[8 * jp + 3])),
                         "r"(pack_bf16(y[8 * jp + 4], y[8 * jp + 5])), "r"(pack_bf16(y[8 * jp + 6], y[8 * jp + 7]))
                         : "memory");
        }
        asm volatile("fence.proxy.async.shared::cta;" ::: "memory");
        wg_bar(bar);
        if (t == 0) {
            asm volatile("cp.async.bulk.tensor.2d.global.shared::cta.bulk_group [%0, {%1, %2}], [%3];"
                         ::"l"(tmo), "r"(0), "r"(d * 32), "r"(sb + O_ST) : "memory");
            asm volatile("cp.async.bulk.commit_group;" ::: "memory");
            asm volatile("cp.async.bulk.wait_group.read 0;" ::: "memory");
        }
        DBG1(8);
    }
}

constexpr int K1_WGS = 5;
constexpr int O_XTRA = K1_WGS * WG_BYTES;
constexpr int K1_SMEM = O_XTRA + 3 * 4096;
constexpr int K1_CTAS = (D_MODEL + K1_WGS - 1) / K1_WGS;
constexpr int K1_STAT = 16;
__device__ __forceinline__ uint32_t raw_box(uint32_t sbase, int i) {
    return i < K1_WGS ? sbase + i * WG_BYTES + O_RAW : sbase + O_XTRA + (i - K1_WGS) * 4096;
}
__device__ __forceinline__ void transpose_window(uint32_t sbase, int warp, int lane, int ch0) {
    const int ch = (lane >> 2) + ch0;
    const uint32_t ub = sbase + ch * WG_BYTES + (lane & 3) * 4;
#pragma unroll
    for (int k = 0; k < 4; k++) {
        const int gi = warp + k * (4 * K1_WGS);
        if (gi < 64) {
            const uint4 v = ldsm_x4_t(raw_box(sbase, gi >> 3) + (gi & 7) * 512 + lane * 16);
            if (ch >= 0 && ch < K1_WGS) {
                const uint32_t a0 = u_addr(ub, 4 * gi);
                sts32(a0, v.x);
                sts32(a0 ^ 16, v.y);
                sts32(a0 ^ 32, v.z);
                sts32(a0 ^ 48, v.w);
            }
        }
    }
}

__global__ void __launch_bounds__(128 * K1_WGS, 1)
ssm_kernel(const __grid_constant__ CUtensorMap tmc, const __grid_constant__ CUtensorMap tmo,
           const bf16* __restrict__ x, const bf16* __restrict__ gw, Params p) {
    extern __shared__ __align__(1024) uint8_t smem_raw[];
    const uint32_t sbase = smem_u32(smem_raw);
    const int tid = threadIdx.x, t = tid & 127, lane = tid & 31;
    const int wg = __shfl_sync(0xffffffffu, tid >> 7, 0), warp = __shfl_sync(0xffffffffu, tid >> 5, 0);
    const int d0 = blockIdx.x * K1_WGS, d = min(d0 + wg, D_MODEL - 1);
    const uint32_t sb = sbase + wg * WG_BYTES;
    const uint32_t xbar = sbase + WG_BYTES - 16;
    const int dw = d0 & ~7;
    const bool two = (d0 & 7) > 3 && dw + 8 < D_MODEL;
    DBG1(0);
    if (blockIdx.x == 0) {
        if (tid == 0) {
            g_epoch = g_epoch + 1;
            asm volatile("fence.acq_rel.gpu;" ::: "memory");
        }
        __syncthreads();
    }
    asm volatile("griddepcontrol.launch_dependents;");
    if (blockIdx.x >= K1_CTAS) {
        const uint32_t tag = (g_stat_epoch[blockIdx.x - K1_CTAS] + 1) & 1u;
        __syncthreads();
        if (tid == 0) g_stat_epoch[blockIdx.x - K1_CTAS] = g_stat_epoch[blockIdx.x - K1_CTAS] + 1;
        uint32_t gr[9];
#pragma unroll
        for (int i = 0; i < 9; i++) gr[i] = __ldg(reinterpret_cast<const uint32_t*>(gw) + lane + 32 * i);
#pragma unroll 1
        for (int row = (blockIdx.x - K1_CTAS) * (4 * K1_WGS) + warp; row < L_SEQ; row += 2 * K1_STAT * 4 * K1_WGS) {
            const int row2 = min(row + K1_STAT * 4 * K1_WGS, L_SEQ - 1);
            uint32_t xr[2][9];
#pragma unroll
            for (int i = 0; i < 9; i++) {
                xr[0][i] = __ldg(reinterpret_cast<const uint32_t*>(x + (size_t)row * D_MODEL) + lane + 32 * i);
                xr[1][i] = __ldg(reinterpret_cast<const uint32_t*>(x + (size_t)row2 * D_MODEL) + lane + 32 * i);
            }
#pragma unroll
            for (int h = 0; h < 2; h++) {
                float s = 0.f, gs = 0.f;
#pragma unroll
                for (int i = 0; i < 9; i++) {
                    s += bf_lo(xr[h][i]) + bf_hi(xr[h][i]);
                    const uint32_t pr = hmul2_bf(xr[h][i], gr[i]);
                    gs += bf_lo(pr) + bf_hi(pr);
                }
#pragma unroll
                for (int o = 16; o; o >>= 1) {
                    s += __shfl_xor_sync(~0u, s, o);
                    gs += __shfl_xor_sync(~0u, gs, o);
                }
                const float mean = s * (1.f / D_MODEL);
                float q = 0.f;
#pragma unroll
                for (int i = 0; i < 9; i++) {
                    const float a = bf_lo(xr[h][i]) - mean, b = bf_hi(xr[h][i]) - mean;
                    q = fmaf(a, a, fmaf(b, b, q));
                }
#pragma unroll
                for (int o = 16; o; o >>= 1) q += __shfl_xor_sync(~0u, q, o);
                if (lane == 0) {
                    const float var = bf16r(q * (1.f / D_MODEL));
                    const float den = bf16r(sqrtf(bf16r(var + 1e-5f)));
                    const int r = h ? row2 : row;
                    const unsigned long long e = ((unsigned long long)((__float_as_uint(__fdividef(1.f, den)) & ~1u) | tag) << 32) |
                                                 pack_bf16(mean, mean);
                    asm volatile("st.relaxed.gpu.global.b64 [%0], %1;" ::"l"(&g_rowstat[r]), "l"(e) : "memory");
                    g_gate[r] = bf16r(__fdividef(1.f, 1.f + __expf(-bf16r(gs))));
                }
            }
        }
        return;
    }
    if (tid == 0) {
        mbar_init(xbar, 1);
        asm volatile("fence.mbarrier_init.release.cluster;" ::: "memory");
        mbar_expect(xbar, 8 * 4096);
#pragma unroll
        for (int i = 0; i < 8; i++) tma2d(raw_box(sbase, i), &tmc, dw, i * 256, xbar);
    }
    const ModeIn mi = load_mode(p, d, t);
    sts128(sb + O_U + t * 16, 0, 0, 0, 0);
    sts128(sb + O_KN + t * 16, 0, 0, 0, 0);
    gen_powers(mi, sb, t);
    DBG1(1);
    asm volatile("fence.proxy.async.shared::cta;" ::: "memory");
    __syncthreads();
    float kd[16];
    WG_FENCE();
    KgenSteps<16>::run(kd, (sb & 0x3FFFF) >> 4);
    WG_COMMIT();
    mbar_wait(xbar, 0);
    DBG1(2);
    transpose_window(sbase, warp, lane, dw - d0);
    if (two) {
        asm volatile("fence.proxy.async.shared::cta;" ::: "memory");
        __syncthreads();
        if (tid == 0) {
            mbar_expect(xbar, 8 * 4096);
#pragma unroll
            for (int i = 0; i < 8; i++) tma2d(raw_box(sbase, i), &tmc, dw + 8, i * 256, xbar);
        }
    }
    DBG1(3);
    WG_WAIT(0);
#pragma unroll
    for (int i = 0; i < 16; i++) asm volatile("" : "+f"(kd[i])::"memory");
    build_tables(kd, mi.dsk, sb, t, 1 + wg);
    if (two) {
        mbar_wait(xbar, 1);
        transpose_window(sbase, warp, lane, dw + 8 - d0);
    }
    asm volatile("fence.proxy.async.shared::cta;" ::: "memory");
    __syncthreads();
    DBG1(5);
    build_windows(sb, t);
    wg_bar(1 + wg);
    DBG1(9);
    if (d0 + wg < D_MODEL) convolve(d, sb, t, 1 + wg, &tmo);
}
}

constexpr int XT_BYTES = 128 * D_MODEL * 2;
constexpr int STAGE_BYTES = 96 * 128;
constexpr int NSTAGE = 6;
constexpr int SM_STAGES = XT_BYTES;
constexpr int SM_BARS = SM_STAGES + NSTAGE * STAGE_BYTES;
constexpr int SM_B1 = SM_BARS + 512;
constexpr int SM_B2 = SM_B1 + 576 * 4;
constexpr int MLP_SMEM = SM_B2 + 576 * 2;
__host__ __device__ constexpr int red_buf(int c) { return c < 7 ? c * 18432 : SM_STAGES + (c - 7) * 18432; }
constexpr int BAR_FULL = 0, BAR_EMPTY = 48, BAR_X = 96, BAR_PARKFREE = 168, BAR_STORED = 176, BAR_LOADED = 248, BAR_A = 320;

__device__ __forceinline__ float gelu2(float x) {
    const float k0 = 0.7978845608028654f, k1 = 0.7978845608028654f * 0.044715f;
    float u = x * fmaf(x * x, k1, k0);
    float th;
    asm("tanh.approx.f32 %0, %1;" : "=f"(th) : "f"(u));
    return fmaf(x, th, x);
}

__device__ __forceinline__ uint32_t gelu2_packed(uint32_t s) {
    const uint32_t k0 = 0x3f4c3f4cu, k1 = 0x3d123d12u;
    uint32_t u = hmul2_bf(s, hfma2_bf(hmul2_bf(s, s), k1, k0)), th;
    asm("tanh.approx.bf16x2 %0, %1;" : "=r"(th) : "r"(u));
    return hfma2_bf(s, th, s);
}
__device__ __forceinline__ void epi_gelu(const float (&acc)[32], int i, uint32_t b1_addr, float r0, float r1,
                                         uint32_t (&o)[4]) {
    float b0, b1, b2, b3;
    asm volatile("ld.shared.v4.f32 {%0,%1,%2,%3}, [%4];"
                 : "=f"(b0), "=f"(b1), "=f"(b2), "=f"(b3) : "r"(b1_addr + i * 16));
    o[0] = pack_bf16(gelu2(fmaf(acc[8 * i + 0], r0, b0)), gelu2(fmaf(acc[8 * i + 1], r0, b1)));
    o[1] = pack_bf16(gelu2(fmaf(acc[8 * i + 2], r1, b0)), gelu2(fmaf(acc[8 * i + 3], r1, b1)));
    o[2] = pack_bf16(gelu2(fmaf(acc[8 * i + 4], r0, b2)), gelu2(fmaf(acc[8 * i + 5], r0, b3)));
    o[3] = pack_bf16(gelu2(fmaf(acc[8 * i + 6], r1, b2)), gelu2(fmaf(acc[8 * i + 7], r1, b3)));
}
__device__ __forceinline__ void epi_park(const float (&acc)[32], int i, uint32_t b1_addr, uint32_t park_addr,
                                         float r0, float r1) {
    uint32_t o[4];
    epi_gelu(acc, i, b1_addr, r0, r1, o);
    asm volatile("st.shared.v4.b32 [%0], {%1,%2,%3,%4};" ::"r"(park_addr + i * 4096), "r"(o[0]), "r"(o[1]),
                 "r"(o[2]), "r"(o[3]) : "memory");
}
__device__ __forceinline__ void epi_part(const float (&acc)[32], int i, uint4* part, uint32_t par) {
    uint4 v;
    v.x = (pack_bf16(acc[8 * i + 0], acc[8 * i + 1]) & ~1u) | par;
    v.y = pack_bf16(acc[8 * i + 2], acc[8 * i + 3]);
    v.z = (pack_bf16(acc[8 * i + 4], acc[8 * i + 5]) & ~1u) | par;
    v.w = pack_bf16(acc[8 * i + 6], acc[8 * i + 7]);
    asm volatile("{\n.reg .b128 q;\nmov.b128 q, {%1, %2};\nst.relaxed.gpu.global.b128 [%0], q;\n}\n" ::"l"(part + i * 32),
                 "l"(((unsigned long long)v.y << 32) | v.x), "l"(((unsigned long long)v.w << 32) | v.z) : "memory");
}
__device__ __forceinline__ void warp_arrive(uint32_t bar, int lane) {
    __syncwarp();
    if (lane == 0) asm volatile("mbarrier.arrive.shared::cta.b64 _, [%0];" ::"r"(bar) : "memory");
}

__device__ __forceinline__ void probe_partials(const uint4* unit, uint32_t par) {
    asm volatile(
        "{\n.reg .pred p;\n.reg .u32 n, v;\nmov.u32 n, 0;\n"
        "PROBE_LOOP:\n"
        "ld.relaxed.gpu.global.u32 v, [%0];\n"
        "xor.b32 v, v, %1;\n"
        "and.b32 v, v, 1;\n"
        "setp.ne.u32 p, v, 0;\n"
        "vote.sync.any.pred p, p, 0xffffffff;\n"
        "@!p bra PROBE_DONE;\n"
        "add.u32 n, n, 1;\n"
        "setp.lt.u32 p, n, 1048576;\n"
        "@p bra PROBE_LOOP;\n"
        "trap;\n"
        "PROBE_DONE:\n}\n" ::"l"(unit), "r"(par) : "memory");
}

template <int EPI>
__device__ __forceinline__ void run_chunk(float (&cur)[32], float (&prev)[32], const uint32_t (&af)[NAF][4],
                                          int parity, uint32_t bars, uint32_t desc0, uint32_t adesc0, uint32_t p0, uint32_t p1,
                                          uint4* part, bool sig, uint32_t rbar, int lane, float r0, float r1) {
#pragma unroll
    for (int s = 0; s < 6; s++) {
        mbar_wait(bars + BAR_FULL + s * 8, parity);
        WG_FENCE();
        mma_stage_rt(s, cur, af, desc0, adesc0);
        WG_COMMIT();
        if (s >= 1 && s <= 4) {
            if (EPI == 1) epi_park(prev, s - 1, p0, p1, r0, r1);
            if (EPI == 2) epi_part(prev, s - 1, part, p1);
        }
        if (s == 4 && EPI == 2) warp_arrive(p0, lane);
        WG_WAIT(1);
        if (sig) asm volatile("mbarrier.arrive.shared::cluster.b64 _, [%0];" ::"r"(rbar + ((s + 5) % 6) * 8) : "memory");
        if (s == 0) fence_acc(prev);
    }
}

__global__ void __cluster_dims__(2, 1, 1) __launch_bounds__(384, 1)
mlp_kernel(const __grid_constant__ CUtensorMap tmx, const __grid_constant__ CUtensorMap tmw1,
           const __grid_constant__ CUtensorMap tmw2, const __grid_constant__ CUtensorMap tma,
           const bf16* __restrict__ b1, const bf16* __restrict__ b2,
           bf16* __restrict__ out) {
    extern __shared__ __align__(1024) uint8_t smem_raw[];
    const uint32_t sbase = smem_u32(smem_raw);
    uint8_t* sgen = smem_raw;
    const int tid = threadIdx.x, lane = tid & 31;
    const int warp = __shfl_sync(0xffffffffu, tid >> 5, 0);
    const int wgid = __shfl_sync(0xffffffffu, tid >> 7, 0);
    const int m = blockIdx.x & 15, f = blockIdx.x >> 4;
    const uint32_t rank = m & 1;
    const uint32_t bars = sbase + SM_BARS;
    if (warp == 0) DBG(12);

    if (tid == 0) {
        if (sbase & 1023) asm volatile("trap;");
        for (int i = 0; i < NSTAGE; i++) {
            mbar_init(bars + BAR_FULL + i * 8, 1);
            mbar_init(bars + BAR_EMPTY + i * 8, 4);
        }
        for (int i = 0; i < 9; i++) mbar_init(bars + BAR_X + i * 8, 1);
        mbar_init(bars + BAR_PARKFREE, 8);
        mbar_init(bars + BAR_A, 1);
        for (int i = 0; i < 9; i++) {
            mbar_init(bars + BAR_STORED + i * 8, 8);
            mbar_init(bars + BAR_LOADED + i * 8, 1);
        }
        asm volatile("fence.mbarrier_init.release.cluster;" ::: "memory");
        for (int j = 0; j < 9; j++) {
            mbar_expect(bars + BAR_X + j * 8, 16384);
            tma2d(sbase + j * 16384, &tmx, j * 64, m * 128, bars + BAR_X + j * 8);
        }
    }
    uint32_t b1v0 = 0, b1v1 = 0;
    if (wgid < 2) {
        const uint32_t* b1w = reinterpret_cast<const uint32_t*>(b1 + f * 576);
        b1v0 = __ldg(b1w + (tid >> 5) * 32 + (tid & 7) * 4 + ((tid >> 3) & 3));
        if (tid < 32) b1v1 = __ldg(b1w + 8 * 32 + (tid & 7) * 4 + ((tid >> 3) & 3));
    }
    __syncthreads();
    asm volatile("barrier.cluster.arrive.relaxed.aligned;\nbarrier.cluster.wait.aligned;" ::: "memory");

    if (warp == 0) DBG(0);
    if (wgid == 2) {
        asm volatile("setmaxnreg.dec.sync.aligned.u32 40;");
        if (warp == 8) {
            if (lane == 0) {
                const uint32_t dst0 = sbase + SM_STAGES + rank * (STAGE_BYTES / 2);
#pragma unroll 1
                for (int cc = 0; cc < 18; cc++) {
                    const CUtensorMap* tm = cc < 9 ? &tmw1 : &tmw2;
                    const int c0 = cc < 9 ? f * 576 + cc * 64 : (cc - 9) * 64;
                    const int c1 = (cc < 9 ? 0 : f * 576) + rank * 48;
                    const int par = (cc & 1) ^ 1;
#pragma unroll
                    for (int s = 0; s < 6; s++) {
                        mbar_wait(bars + BAR_EMPTY + s * 8, par);
                        mbar_expect(bars + BAR_FULL + s * 8, STAGE_BYTES);
                        tma2d_mc(dst0 + s * STAGE_BYTES, tm, c0, c1 + s * 96, bars + BAR_FULL + s * 8, 3);
                    }
                }
            }
        } else if (warp == 9) {
            {
                uint32_t* b2s = reinterpret_cast<uint32_t*>(sgen + SM_B2);
                for (int w = lane; w < 288; w += 32) {
                    const int jj = w & 1, q = (w >> 1) & 3, ci = w >> 3;
                    b2s[w] = __ldg(reinterpret_cast<const uint32_t*>(b2) + ci * 8 + jj * 4 + q);
                }
                __syncwarp();
            }
            asm volatile("griddepcontrol.wait;" ::: "memory");
            const uint32_t par = __ldcg(&g_epoch);
            mbar_wait(bars + BAR_PARKFREE, 0);
            asm volatile("fence.proxy.async.shared::cta;" ::: "memory");
            const uint4* psrc = g_part + (m * 9 * 8 + f) * (8 * 4 * 32);
#pragma unroll 1
            for (int c = 0; c < 9; c++) {
                const uint32_t buf = sbase + red_buf(c);
                if (c == 7) {
                    mbar_wait(bars + BAR_EMPTY + 0, 1);
                    mbar_wait(bars + BAR_EMPTY + 8, 1);
                    mbar_wait(bars + BAR_EMPTY + 16, 1);
                }
                if (lane == 0) {
                    mbar_expect(bars + BAR_LOADED + c * 8, 16384 + 2048);
                    tma2d(buf + 16384, &tma, m * 128 + f * 16, c * 64, bars + BAR_LOADED + c * 8);
                }
                mbar_wait(bars + BAR_STORED + c * 8, 0);
                probe_partials(psrc + (lane & 7) * 128 + 96 + 31, par);
                DBG(16 + c);
                if (lane == 0)
                    asm volatile("cp.async.bulk.shared::cluster.global.mbarrier::complete_tx::bytes [%0], [%1], 16384, [%2];"
                                 ::"r"(buf), "l"(psrc), "r"(bars + BAR_LOADED + c * 8) : "memory");
                psrc += 8 * 8 * 4 * 32;
            }
        }
        __syncwarp();
        asm volatile("barrier.cluster.arrive.release.aligned;\nbarrier.cluster.wait.acquire.aligned;" ::: "memory");
    } else {
        asm volatile("setmaxnreg.inc.sync.aligned.u32 232;");
        const uint32_t par = __ldcg(&g_epoch) & 1u;
        uint2 rs0, rs1;
        {
            const uint2* rp = &g_rowstat[m * 128 + warp * 16 + (lane >> 2)];
            int tries = 0;
            while (true) {
                unsigned long long e0, e1;
                asm volatile("ld.relaxed.gpu.global.b64 %0, [%1];" : "=l"(e0) : "l"(rp) : "memory");
                asm volatile("ld.relaxed.gpu.global.b64 %0, [%1];" : "=l"(e1) : "l"(rp + 8) : "memory");
                rs0 = make_uint2((uint32_t)e0, (uint32_t)(e0 >> 32));
                rs1 = make_uint2((uint32_t)e1, (uint32_t)(e1 >> 32));
                if (!__any_sync(0xffffffffu, ((rs0.y ^ par) | (rs1.y ^ par)) & 1)) break;
                if (++tries > (1 << 22)) asm volatile("trap;");
            }
        }
        const int g = lane >> 2, tq = lane & 3;
        uint32_t af[NAF][4];
        float acc0[32], acc1[32];
        const bool sig = (tid & 127) < 2;
        uint32_t rbar;
        asm volatile("mapa.shared::cluster.u32 %0, %1, %2;" : "=r"(rbar) : "r"(bars + BAR_EMPTY), "r"(tid & 1));
        const uint32_t desc0 = ((sbase + SM_STAGES) & 0x3FFFF) >> 4;
        const uint32_t adesc0 = ((sbase + 8 * 16384 + wgid * 8192) & 0x3FFFF) >> 4;

        {
            float2* b1s = reinterpret_cast<float2*>(sgen + SM_B1);
            b1s[tid] = make_float2(bf_lo(b1v0), bf_hi(b1v0));
            if (tid < 32) b1s[256 + tid] = make_float2(bf_lo(b1v1), bf_hi(b1v1));
        }
        const float rstd0 = __uint_as_float(rs0.y), rstd1 = __uint_as_float(rs1.y);
        {
            const int lrow = warp * 16 + (lane & 7) + ((lane >> 3) & 1) * 8;
            const uint32_t rbase = sbase + lrow * 128;
            const int hi = lane >> 4, sw = lrow & 7;
#pragma unroll
            for (int s = 0; s < 6; s++) {
#pragma unroll
                for (int k = s * 6; k < s * 6 + 6; k++) {
                    const int j = k >> 2, kk = k & 3;
                    if (kk == 0 || k == s * 6) mbar_wait(bars + BAR_X + j * 8, 0);
                    uint32_t tmp[4];
                    uint32_t (&a)[4] = (k < NAF) ? af[(k < NAF) ? k : 0] : tmp;
                    const uint32_t addr = rbase + j * 16384 + (((kk * 2 + hi) ^ sw) << 4);
                    ldsm_x4(a, addr);
                    a[0] = hsub2_bf(a[0], rs0.x);
                    a[1] = hsub2_bf(a[1], rs1.x);
                    a[2] = hsub2_bf(a[2], rs0.x);
                    a[3] = hsub2_bf(a[3], rs1.x);
                    if (k >= NAF) stsm_x4(a, addr);
                }
                if (s == 5) {
                    asm volatile("fence.proxy.async.shared::cta;" ::: "memory");
                    asm volatile("bar.sync %0, 128;" ::"r"(3 + wgid) : "memory");
                    if (warp == 0) DBG(1);
                }
                mbar_wait(bars + BAR_FULL + s * 8, 0);
                WG_FENCE();
                mma_stage_rt(s, acc0, af, desc0, adesc0);
                WG_COMMIT();
                if (s > 0) {
                    WG_WAIT(1);
                    if (sig) asm volatile("mbarrier.arrive.shared::cluster.b64 _, [%0];" ::"r"(rbar + (s - 1) * 8) : "memory");
                }
            }
            asm volatile("bar.sync 1, 256;" ::: "memory");
        }
        {
            uint32_t b1a = sbase + SM_B1 + tq * 64, park = sbase + tid * 16;
#pragma unroll 1
            for (int c = 1; c < 9; c += 2) {
                if (warp == 0) DBG(2 + (c >> 1));
                run_chunk<1>(acc1, acc0, af, 1, bars, desc0, adesc0, b1a, park, nullptr, sig, rbar, lane, rstd0, rstd1);
                run_chunk<1>(acc0, acc1, af, 0, bars, desc0, adesc0, b1a + 256, park + 16384, nullptr, sig, rbar, lane, rstd0, rstd1);
                b1a += 512;
                park += 32768;
            }
        }
        if (warp == 0) DBG(6);
        WG_WAIT(0);
        if (sig) asm volatile("mbarrier.arrive.shared::cluster.b64 _, [%0];" ::"r"(rbar + 5 * 8) : "memory");
        fence_acc(acc0);
#pragma unroll
        for (int k = 0; k < 32; k++)
            asm volatile("ld.shared.v4.b32 {%0,%1,%2,%3}, [%4];"
                         : "=r"(af[k][0]), "=r"(af[k][1]), "=r"(af[k][2]), "=r"(af[k][3])
                         : "r"(sbase + tid * 16 + k * 4096) : "memory");
        {
#pragma unroll
            for (int s = 0; s < 6; s++) {
                mbar_wait(bars + BAR_FULL + s * 8, 1);
                WG_FENCE();
                mma_stage_rt(s, acc1, af, desc0, adesc0);
                WG_COMMIT();
                if (s < 2) epi_gelu(acc0, s, sbase + SM_B1 + tq * 64 + 8 * 256, rstd0, rstd1, af[32 + (s & 1)]);
                if (s == 2 || s == 3) {
                    uint32_t tmp[4];
                    epi_gelu(acc0, s, sbase + SM_B1 + tq * 64 + 8 * 256, rstd0, rstd1, tmp);
                    const int lrow = warp * 16 + (lane & 7) + ((lane >> 3) & 1) * 8;
                    stsm_x4(tmp, sbase + 8 * 16384 + lrow * 128 + (((s * 2 + (lane >> 4)) ^ (lrow & 7)) << 4));
                }
                if (s == 3) {
                    asm volatile("fence.proxy.async.shared::cta;" ::: "memory");
                    asm volatile("bar.sync %0, 128;" ::"r"(3 + wgid) : "memory");
                }
                if (s > 0) {
                    WG_WAIT(1);
                    if (sig) asm volatile("mbarrier.arrive.shared::cluster.b64 _, [%0];" ::"r"(rbar + (s - 1) * 8) : "memory");
                }
                if (s == 5) warp_arrive(bars + BAR_PARKFREE, lane);
            }
        }
        uint4* part = g_part + (size_t)((m * 9 * 8 + warp) * 8 + f) * (4 * 32) + lane;
        uint32_t stored = bars + BAR_STORED;
#pragma unroll 1
        for (int c = 1; c < 9; c += 2) {
            if (warp == 0) DBG(7 + (c >> 1));
            run_chunk<2>(acc0, acc1, af, 0, bars, desc0, adesc0, stored, par, part, sig, rbar, lane, 0.f, 0.f);
            run_chunk<2>(acc1, acc0, af, 1, bars, desc0, adesc0, stored + 8, par, part + 8 * 8 * 4 * 32, sig, rbar, lane, 0.f, 0.f);
            part += 2 * 8 * 8 * 4 * 32;
            stored += 16;
        }
        const int t0 = m * 128 + f * 16 + g;
        asm volatile("griddepcontrol.wait;" ::: "memory");
        const float g0 = __ldcg(&g_gate[t0]), g1 = __ldcg(&g_gate[t0 + 8]);
        WG_WAIT(0);
        fence_acc(acc1);
#pragma unroll
        for (int i = 0; i < 4; i++) epi_part(acc1, i, part, par);
        warp_arrive(stored, lane);
        if (warp == 0) DBG(11);
        {
            const uint32_t gA = pack_bf16(g0, g0), gB = pack_bf16(g1, g1);
            const uint32_t half2 = 0x3f003f00u, one2 = 0x3f803f80u;
            const uint32_t oA = hsub2_bf(one2, gA), oB = hsub2_bf(one2, gB);
            uint32_t* o32 = reinterpret_cast<uint32_t*>(out + (size_t)t0 * D_MODEL + 2 * tq) + warp * 4;
            const uint32_t lm = sbase + 16384 + (lane & 7) * 32 + ((lane >> 3) & 1) * 16 + warp * 256;
            const uint32_t a0 = sbase + (warp >> 1) * 512 + lane * 16 + (warp & 1) * 8;
            const uint32_t b2a = sbase + SM_B2 + (warp >> 1) * 32 + tq * 8 + (warp & 1) * 4;
#pragma unroll 1
            for (int c0 = 0; c0 < 9; c0 += 3) {
                uint2 v[3][8], av[3];
                uint32_t bb[3];
#pragma unroll
                for (int k = 0; k < 3; k++) {
                    const int c = c0 + k;
                    const uint32_t bo = red_buf(c);
                    mbar_wait(bars + BAR_LOADED + c * 8, 0);
#pragma unroll
                    for (int q = 0; q < 8; q++) v[k][q] = ssm::lds64(a0 + bo + q * 2048);
                    asm volatile("ldmatrix.sync.aligned.m8n8.x2.trans.shared.b16 {%0,%1}, [%2];"
                                 : "=r"(av[k].x), "=r"(av[k].y) : "r"(lm + bo) : "memory");
                    bb[k] = ssm::lds32(b2a + c * 128);
                }
                uint32_t bad = 0;
#pragma unroll
                for (int k = 0; k < 3; k++)
#pragma unroll
                    for (int q = 0; q < 8; q++) bad |= v[k][q].x ^ par;
                int tries = 0;
                while (__any_sync(0xffffffffu, bad & 1)) {
                    const uint2* ps = reinterpret_cast<const uint2*>(
                        g_part + ((m * 9 + c0) * 8 + f) * (8 * 4 * 32) + (warp >> 1) * 32 + lane) + (warp & 1);
                    bad = 0;
#pragma unroll
                    for (int k = 0; k < 3; k++)
#pragma unroll
                        for (int q = 0; q < 8; q++) {
                            unsigned long long w;
                            asm volatile("ld.relaxed.gpu.global.b64 %0, [%1];" : "=l"(w)
                                         : "l"(ps + k * (8 * 8 * 4 * 32 * 2) + q * 256) : "memory");
                            v[k][q] = make_uint2((uint32_t)w, (uint32_t)(w >> 32));
                            bad |= v[k][q].x ^ par;
                        }
                    if (++tries > (1 << 20)) asm volatile("trap;");
                }
#pragma unroll
                for (int k = 0; k < 3; k++) {
                    float sx0 = 0.f, sx1 = 0.f, sy0 = 0.f, sy1 = 0.f;
#pragma unroll
                    for (int q = 0; q < 8; q++) {
                        sx0 += bf_lo(v[k][q].x); sx1 += bf_hi(v[k][q].x);
                        sy0 += bf_lo(v[k][q].y); sy1 += bf_hi(v[k][q].y);
                    }
                    o32[(c0 + k) * 32] = hadd2_bf(hmul2_bf(gA, av[k].x), hmul2_bf(oA, hfma2_bf(pack_bf16(sx0, sx1), half2, bb[k])));
                    o32[(c0 + k) * 32 + 4 * D_MODEL] =
                        hadd2_bf(hmul2_bf(gB, av[k].y), hmul2_bf(oB, hfma2_bf(pack_bf16(sy0, sy1), half2, bb[k])));
                }
                if (warp == 0) DBG(32 + c0 / 3);
            }
        }
        asm volatile("barrier.cluster.arrive.release.aligned;\nbarrier.cluster.wait.acquire.aligned;" ::: "memory");
        if (warp == 0) DBG(13);
    }
}

typedef CUresult (*EncodeFn)(CUtensorMap*, CUtensorMapDataType, cuuint32_t, void*, const cuuint64_t*,
                             const cuuint64_t*, const cuuint32_t*, const cuuint32_t*, CUtensorMapInterleave,
                             CUtensorMapSwizzle, CUtensorMapL2promotion, CUtensorMapFloatOOBfill);

static void make_map(EncodeFn enc, CUtensorMap* m, const void* ptr, uint64_t cols, uint64_t rows, uint32_t box_c,
                     uint32_t box_r, CUtensorMapSwizzle swz = CU_TENSOR_MAP_SWIZZLE_128B) {
    cuuint64_t dim[2] = {cols, rows};
    cuuint64_t str[1] = {cols * 2};
    cuuint32_t box[2] = {box_c, box_r};
    cuuint32_t es[2] = {1, 1};
    enc(m, CU_TENSOR_MAP_DATA_TYPE_BFLOAT16, 2, const_cast<void*>(ptr), dim, str, box, es,
        CU_TENSOR_MAP_INTERLEAVE_NONE, swz, CU_TENSOR_MAP_L2_PROMOTION_L2_128B,
        CU_TENSOR_MAP_FLOAT_OOB_FILL_NONE);
}

}

extern "C" void kernel_launch(void* const* d_in, const int* in_sizes, int n_in, void* d_out, int out_size) {
    const bf16* u = (const bf16*)d_in[0];
    const bf16* A_re = (const bf16*)d_in[1];
    const bf16* A_im = (const bf16*)d_in[2];
    const bf16* B_re = (const bf16*)d_in[3];
    const bf16* B_im = (const bf16*)d_in[4];
    const bf16* C_re = (const bf16*)d_in[5];
    const bf16* C_im = (const bf16*)d_in[6];
    const bf16* log_dt = (const bf16*)d_in[7];
    const bf16* Dskip = (const bf16*)d_in[8];
    const bf16* w1 = (const bf16*)d_in[10];
    const bf16* b1 = (const bf16*)d_in[11];
    const bf16* w2 = (const bf16*)d_in[12];
    const bf16* b2 = (const bf16*)d_in[13];
    const bf16* gw = (const bf16*)d_in[14];
    bf16* out = (bf16*)d_out;

    static EncodeFn enc = nullptr;
    if (!enc) {
        void* fn = nullptr;
        cudaDriverEntryPointQueryResult q;
        cudaGetDriverEntryPoint("cuTensorMapEncodeTiled", &fn, cudaEnableDefault, &q);
        enc = (EncodeFn)fn;
        cudaFuncSetAttribute(mlp_kernel, cudaFuncAttributeMaxDynamicSharedMemorySize, MLP_SMEM);
        cudaFuncSetAttribute(ssm::ssm_kernel, cudaFuncAttributeMaxDynamicSharedMemorySize, ssm::K1_SMEM);
    }
    static void* aT_ptr = nullptr;
    if (!aT_ptr) cudaGetSymbolAddress(&aT_ptr, g_aT);
    CUtensorMap tmx, tmw1, tmw2, tma;
    make_map(enc, &tma, aT_ptr, L_SEQ, D_MODEL, 16, 64, CU_TENSOR_MAP_SWIZZLE_NONE);
    make_map(enc, &tmx, u, D_MODEL, L_SEQ, 64, 128);
    make_map(enc, &tmw1, w1, F_DIM, D_MODEL, 64, 48);
    make_map(enc, &tmw2, w2, D_MODEL, F_DIM, 64, 48);

    cudaStream_t st = cudaStreamPerThread;
    ssm::Params sp{A_re, A_im, B_re, B_im, C_re, C_im, log_dt, Dskip};
    CUtensorMap tmc, tmo;
    make_map(enc, &tmc, u, D_MODEL, L_SEQ, 8, 256, CU_TENSOR_MAP_SWIZZLE_NONE);
    make_map(enc, &tmo, aT_ptr, 64, D_MODEL * 32, 64, 32);
    ssm::ssm_kernel<<<ssm::K1_CTAS + ssm::K1_STAT, 128 * ssm::K1_WGS, ssm::K1_SMEM, st>>>(tmc, tmo, u, gw, sp);
    cudaLaunchConfig_t cfg = {};
    cfg.gridDim = dim3(128);
    cfg.blockDim = dim3(384);
    cfg.dynamicSmemBytes = MLP_SMEM;
    cfg.stream = st;
    cudaLaunchAttribute at[1];
    at[0].id = cudaLaunchAttributeProgrammaticStreamSerialization;
    at[0].val.programmaticStreamSerializationAllowed = 1;
    cfg.attrs = at;
    cfg.numAttrs = 1;
    cudaLaunchKernelEx(&cfg, mlp_kernel, tmx, tmw1, tmw2, tma, b1, b2, out);
}
```

```cpp
#include <cuda_runtime.h>
#include <cuda_bf16.h>
#include <cuda.h>
#include <stdint.h>

namespace {

constexpr int L_SEQ = 2048;
constexpr int D_MODEL = 576;
constexpr int F_DIM = 4608;
constexpr int N_MODES = 128;

typedef __nv_bfloat16 bf16;

__device__ uint2 g_rowstat[L_SEQ];
__device__ float g_gate[L_SEQ];
__device__ bf16 g_aT[D_MODEL * L_SEQ];
__device__ uint4 g_part[16 * 9 * 8 * 8 * 4 * 32];
__device__ unsigned g_stat_epoch[16];
__device__ unsigned g_epoch;

#define DBG(slot)
#define DBG1(slot)

__device__ __forceinline__ uint32_t smem_u32(const void* p) { return (uint32_t)__cvta_generic_to_shared(p); }
__device__ __forceinline__ float bf16r(float x) { return __bfloat162float(__float2bfloat16_rn(x)); }
__device__ __forceinline__ uint32_t pack_bf16(float lo, float hi) {
    uint32_t r;
    asm("cvt.rn.bf16x2.f32 %0, %1, %2;" : "=r"(r) : "f"(hi), "f"(lo));
    return r;
}
__device__ __forceinline__ float bf_lo(uint32_t v) { return __uint_as_float(v << 16); }
__device__ __forceinline__ float bf_hi(uint32_t v) { return __uint_as_float(v & 0xffff0000u); }

__device__ __forceinline__ void mbar_init(uint32_t bar, int cnt) {
    asm volatile("mbarrier.init.shared::cta.b64 [%0], %1;" ::"r"(bar), "r"(cnt));
}
__device__ __forceinline__ void mbar_expect(uint32_t bar, int bytes) {
    asm volatile("mbarrier.arrive.expect_tx.shared::cta.b64 _, [%0], %1;" ::"r"(bar), "r"(bytes) : "memory");
}
__device__ __forceinline__ void mbar_wait(uint32_t bar, int parity) {
    asm volatile(
        "{\n.reg .pred p;\n.reg .u32 n;\nmov.u32 n, 0;\n"
        "WAIT_LOOP:\n"
        "mbarrier.try_wait.parity.shared::cta.b64 p, [%0], %1;\n"
        "@p bra WAIT_DONE;\n"
        "add.u32 n, n, 1;\n"
        "setp.lt.u32 p, n, 4194304;\n"
        "@p bra WAIT_LOOP;\n"
        "trap;\n"
        "WAIT_DONE:\n}\n" ::"r"(bar), "r"(parity) : "memory");
}
__device__ __forceinline__ void tma2d(uint32_t dst, const CUtensorMap* m, int c0, int c1, uint32_t bar) {
    asm volatile(
        "cp.async.bulk.tensor.2d.shared::cluster.global.mbarrier::complete_tx::bytes [%0], [%1, {%3,%4}], [%2];"
        ::"r"(dst), "l"(m), "r"(bar), "r"(c0), "r"(c1) : "memory");
}
__device__ __forceinline__ void tma2d_mc(uint32_t dst, const CUtensorMap* m, int c0, int c1, uint32_t bar,
                                         uint16_t mask) {
    asm volatile(
        "cp.async.bulk.tensor.2d.shared::cluster.global.mbarrier::complete_tx::bytes.multicast::cluster.L2::cache_hint "
        "[%0], [%1, {%3,%4}], [%2], %5, %6;"
        ::"r"(dst), "l"(m), "r"(bar), "r"(c0), "r"(c1), "h"(mask), "l"(0x12F0000000000000ull) : "memory");
}
__device__ __forceinline__ void ldsm_x4(uint32_t (&r)[4], uint32_t addr) {
    asm volatile("ldmatrix.sync.aligned.m8n8.x4.shared.b16 {%0,%1,%2,%3}, [%4];"
                 : "=r"(r[0]), "=r"(r[1]), "=r"(r[2]), "=r"(r[3]) : "r"(addr) : "memory");
}
#define WG_FENCE() asm volatile("wgmma.fence.sync.aligned;\n" ::: "memory")
#define WG_COMMIT() asm volatile("wgmma.commit_group.sync.aligned;\n" ::: "memory")
#define WG_WAIT(n) asm volatile("wgmma.wait_group.sync.aligned %0;\n" ::"n"(n) : "memory")

template <int SCALE_D, int OFF>
__device__ __forceinline__ void wgmma_rs_n64(float (&d)[32], const uint32_t (&a)[4], uint32_t desc_lo) {
    asm volatile(
        "{\n.reg .pred p;\n.reg .b32 lo;\n.reg .b64 dsc;\nsetp.ne.b32 p, %37, 0;\n"
        "add.u32 lo, %36, %38;\nmov.b64 dsc, {lo, 0x40000040};\n"
        "wgmma.mma_async.sync.aligned.m64n64k16.f32.bf16.bf16 "
        "{%0,%1,%2,%3,%4,%5,%6,%7,%8,%9,%10,%11,%12,%13,%14,%15,%16,%17,%18,%19,%20,%21,%22,%23,%24,%25,%26,%27,%28,%29,%30,%31},"
        "{%32,%33,%34,%35}, dsc, p, 1, 1, 1;\n}\n"
        : "+f"(d[0]), "+f"(d[1]), "+f"(d[2]), "+f"(d[3]), "+f"(d[4]), "+f"(d[5]), "+f"(d[6]), "+f"(d[7]),
          "+f"(d[8]), "+f"(d[9]), "+f"(d[10]), "+f"(d[11]), "+f"(d[12]), "+f"(d[13]), "+f"(d[14]), "+f"(d[15]),
          "+f"(d[16]), "+f"(d[17]), "+f"(d[18]), "+f"(d[19]), "+f"(d[20]), "+f"(d[21]), "+f"(d[22]), "+f"(d[23]),
          "+f"(d[24]), "+f"(d[25]), "+f"(d[26]), "+f"(d[27]), "+f"(d[28]), "+f"(d[29]), "+f"(d[30]), "+f"(d[31])
        : "r"(a[0]), "r"(a[1]), "r"(a[2]), "r"(a[3]), "r"(desc_lo), "n"(SCALE_D), "n"(OFF));
}
template <int OFF, int AOFF>
__device__ __forceinline__ void wgmma_ss_n64(float (&d)[32], uint32_t adesc_lo, uint32_t desc_lo) {
    asm volatile(
        "{\n.reg .pred p;\n.reg .b32 lo;\n.reg .b64 dsc, dsa;\nsetp.ne.b32 p, 1, 0;\n"
        "add.u32 lo, %33, %34;\nmov.b64 dsc, {lo, 0x40000040};\n"
        "add.u32 lo, %32, %35;\nmov.b64 dsa, {lo, 0x40000040};\n"
        "wgmma.mma_async.sync.aligned.m64n64k16.f32.bf16.bf16 "
        "{%0,%1,%2,%3,%4,%5,%6,%7,%8,%9,%10,%11,%12,%13,%14,%15,%16,%17,%18,%19,%20,%21,%22,%23,%24,%25,%26,%27,%28,%29,%30,%31},"
        "dsa, dsc, p, 1, 1, 0, 1;\n}\n"
        : "+f"(d[0]), "+f"(d[1]), "+f"(d[2]), "+f"(d[3]), "+f"(d[4]), "+f"(d[5]), "+f"(d[6]), "+f"(d[7]),
          "+f"(d[8]), "+f"(d[9]), "+f"(d[10]), "+f"(d[11]), "+f"(d[12]), "+f"(d[13]), "+f"(d[14]), "+f"(d[15]),
          "+f"(d[16]), "+f"(d[17]), "+f"(d[18]), "+f"(d[19]), "+f"(d[20]), "+f"(d[21]), "+f"(d[22]), "+f"(d[23]),
          "+f"(d[24]), "+f"(d[25]), "+f"(d[26]), "+f"(d[27]), "+f"(d[28]), "+f"(d[29]), "+f"(d[30]), "+f"(d[31])
        : "r"(adesc_lo), "r"(desc_lo), "n"(OFF), "n"(AOFF));
}
constexpr int NAF = 34;
template <int S, int FIRST>
__device__ __forceinline__ void mma_stage(float (&d)[32], const uint32_t (&af)[NAF][4], uint32_t desc_lo,
                                          uint32_t adesc_lo) {
    constexpr int B = (S * 96 * 128) >> 4;
    wgmma_rs_n64<FIRST ? 0 : 1, B + 0 * 128>(d, af[S * 6 + 0], desc_lo);
    wgmma_rs_n64<1, B + 1 * 128>(d, af[S * 6 + 1], desc_lo);
    wgmma_rs_n64<1, B + 2 * 128>(d, af[S * 6 + 2], desc_lo);
    wgmma_rs_n64<1, B + 3 * 128>(d, af[S * 6 + 3], desc_lo);
    if constexpr (S < 5) {
        wgmma_rs_n64<1, B + 4 * 128>(d, af[S * 6 + 4], desc_lo);
        wgmma_rs_n64<1, B + 5 * 128>(d, af[S * 6 + 5], desc_lo);
    } else {
        wgmma_ss_n64<B + 4 * 128, 4>(d, adesc_lo, desc_lo);
        wgmma_ss_n64<B + 5 * 128, 6>(d, adesc_lo, desc_lo);
    }
}
__device__ __forceinline__ void mma_stage_rt(int s, float (&d)[32], const uint32_t (&af)[NAF][4], uint32_t desc_lo,
                                             uint32_t adesc_lo) {
    if (s == 0) mma_stage<0, 1>(d, af, desc_lo, adesc_lo);
    if (s == 1) mma_stage<1, 0>(d, af, desc_lo, adesc_lo);
    if (s == 2) mma_stage<2, 0>(d, af, desc_lo, adesc_lo);
    if (s == 3) mma_stage<3, 0>(d, af, desc_lo, adesc_lo);
    if (s == 4) mma_stage<4, 0>(d, af, desc_lo, adesc_lo);
    if (s == 5) mma_stage<5, 0>(d, af, desc_lo, adesc_lo);
}
__device__ __forceinline__ void stsm_x4(const uint32_t (&r)[4], uint32_t addr) {
    asm volatile("stmatrix.sync.aligned.m8n8.x4.shared.b16 [%4], {%0,%1,%2,%3};"
                 ::"r"(r[0]), "r"(r[1]), "r"(r[2]), "r"(r[3]), "r"(addr) : "memory");
}
__device__ __forceinline__ void fence_acc(float (&d)[32]) {
#pragma unroll
    for (int i = 0; i < 32; i++) asm volatile("" : "+f"(d[i])::"memory");
}

__device__ __forceinline__ uint32_t hadd2_bf(uint32_t a, uint32_t b) {
    uint32_t r;
    asm("add.rn.bf16x2 %0, %1, %2;" : "=r"(r) : "r"(a), "r"(b));
    return r;
}
__device__ __forceinline__ uint32_t hsub2_bf(uint32_t a, uint32_t b) {
    uint32_t r;
    asm("sub.rn.bf16x2 %0, %1, %2;" : "=r"(r) : "r"(a), "r"(b));
    return r;
}
__device__ __forceinline__ uint32_t hmul2_bf(uint32_t a, uint32_t b) {
    uint32_t r;
    asm("mul.rn.bf16x2 %0, %1, %2;" : "=r"(r) : "r"(a), "r"(b));
    return r;
}
__device__ __forceinline__ uint32_t hfma2_bf(uint32_t a, uint32_t b, uint32_t c) {
    uint32_t r;
    asm("fma.rn.bf16x2 %0, %1, %2, %3;" : "=r"(r) : "r"(a), "r"(b), "r"(c));
    return r;
}
namespace ssm {
constexpr int O_H = 0;
constexpr int O_L = 12288;
constexpr int HL_END = O_L + 16384;
constexpr int O_Q = 0;
constexpr int O_Q12 = 5120;
constexpr int O_Q34 = O_Q12 + 1280;
constexpr int O_Y12 = O_Q34 + 2048 - 2176;
constexpr int O_Y34 = O_Y12 + 8704 - 4352;
constexpr int O_W3 = O_Y34 + 8704 + 256;
constexpr int O_W4 = O_W3 + 2048 + 256;
constexpr int O_W5 = O_W4 + 2048;
constexpr int O_U = HL_END;
constexpr int O_RAW = O_U + 6144;
constexpr int O_W1 = O_U + 6144 + 256;
constexpr int O_W2 = O_W1 + 3072 + 256;
constexpr int O_ST = O_RAW;
constexpr int O_KN = O_W2 + 3072;
constexpr int O_A12 = O_KN + 1344;
constexpr int O_A3 = O_A12 + 384;
constexpr int O_KQ = O_A3 + 304;
constexpr int WG_BYTES = 44032;
static_assert(O_W5 + 2048 <= HL_END && O_KQ + 16 <= WG_BYTES && WG_BYTES % 1024 == 0 && O_RAW + 8192 <= WG_BYTES, "map");

struct cplx { float r, i; };
__device__ __forceinline__ cplx cmul(cplx a, cplx b) {
    cplx o;
    o.r = fmaf(a.r, b.r, -a.i * b.i);
    o.i = fmaf(a.r, b.i, a.i * b.r);
    return o;
}
__device__ __forceinline__ cplx cexp_l(float lr, float li, float l) {
    const float e = exp2f((lr * l) * 1.4426950408889634f);
    const float ang = li * l;
    const float k = rintf(ang * 0.15915494309189535f);
    float r = fmaf(k, -6.2831854820251465f, ang);
    r = fmaf(k, 1.7484556000744487e-07f, r);
    cplx o;
    o.r = e * __cosf(r);
    o.i = e * __sinf(r);
    return o;
}
template <typename T> __device__ __forceinline__ T* sp(uint32_t a) {
    return reinterpret_cast<T*>(__cvta_shared_to_generic(a));
}
__device__ __forceinline__ void sts32(uint32_t a, uint32_t v) { *sp<uint32_t>(a) = v; }
__device__ __forceinline__ void sts16(uint32_t a, uint32_t v) { *sp<unsigned short>(a) = (unsigned short)v; }
__device__ __forceinline__ uint32_t lds16(uint32_t a) { return *sp<unsigned short>(a); }
__device__ __forceinline__ uint32_t lds32(uint32_t a) { return *sp<uint32_t>(a); }
__device__ __forceinline__ float ldsf(uint32_t a) { return *sp<float>(a); }
__device__ __forceinline__ uint2 lds64(uint32_t a) { return *sp<uint2>(a); }
__device__ __forceinline__ void sts64(uint32_t a, uint32_t x, uint32_t y) { *sp<uint2>(a) = make_uint2(x, y); }
__device__ __forceinline__ void sts64f(uint32_t a, float x, float y) { *sp<float2>(a) = make_float2(x, y); }
__device__ __forceinline__ void sts128(uint32_t a, uint32_t x, uint32_t y, uint32_t z, uint32_t w) {
    *sp<uint4>(a) = make_uint4(x, y, z, w);
}
__device__ __forceinline__ uint4 lds128(uint32_t a) { return *sp<uint4>(a); }
__device__ __forceinline__ void wg_bar(int id) { asm volatile("bar.sync %0, 128;" ::"r"(id) : "memory"); }
__device__ __forceinline__ uint32_t u_addr(uint32_t sb, int grp) {
    const int gq = grp + 128;
    return sb + O_U + (gq >> 3) * 128 + (((gq ^ (gq >> 3)) & 7) << 4);
}
template <int SCALE_D, int OA, int OB>
__device__ __forceinline__ void wgmma_ss_n32(float (&d)[16], uint32_t dl) {
    asm volatile(
        "{\n.reg .pred p;\n.reg .b32 lo;\n.reg .b64 x, y;\nsetp.ne.b32 p, %17, 0;\n"
        "add.u32 lo, %16, %18;\nmov.b64 x, {lo, 0x40000040};\nadd.u32 lo, %16, %19;\nmov.b64 y, {lo, 0x40000040};\n"
        "wgmma.mma_async.sync.aligned.m64n32k16.f32.bf16.bf16 "
        "{%0,%1,%2,%3,%4,%5,%6,%7,%8,%9,%10,%11,%12,%13,%14,%15}, x, y, p, 1, 1, 0, 0;\n}\n"
        : "+f"(d[0]), "+f"(d[1]), "+f"(d[2]), "+f"(d[3]), "+f"(d[4]), "+f"(d[5]), "+f"(d[6]), "+f"(d[7]),
          "+f"(d[8]), "+f"(d[9]), "+f"(d[10]), "+f"(d[11]), "+f"(d[12]), "+f"(d[13]), "+f"(d[14]), "+f"(d[15])
        : "r"(dl), "n"(SCALE_D), "n"(OA), "n"(OB));
}
template <int OB>
__device__ __forceinline__ void wgmma_rs_n32(float (&d)[16], uint32_t a0, uint32_t a1, uint32_t a2, uint32_t a3,
                                             uint32_t dl) {
    asm volatile(
        "{\n.reg .pred p;\n.reg .b32 lo;\n.reg .b64 y;\nsetp.ne.b32 p, 1, 0;\n"
        "add.u32 lo, %20, %21;\nmov.b64 y, {lo, 0x40000040};\n"
        "wgmma.mma_async.sync.aligned.m64n32k16.f32.bf16.bf16 "
        "{%0,%1,%2,%3,%4,%5,%6,%7,%8,%9,%10,%11,%12,%13,%14,%15}, {%16,%17,%18,%19}, y, p, 1, 1, 0;\n}\n"
        : "+f"(d[0]), "+f"(d[1]), "+f"(d[2]), "+f"(d[3]), "+f"(d[4]), "+f"(d[5]), "+f"(d[6]), "+f"(d[7]),
          "+f"(d[8]), "+f"(d[9]), "+f"(d[10]), "+f"(d[11]), "+f"(d[12]), "+f"(d[13]), "+f"(d[14]), "+f"(d[15])
        : "r"(a0), "r"(a1), "r"(a2), "r"(a3), "r"(dl), "n"(OB));
}
template <int KS> struct KgenSteps {
    static __device__ __forceinline__ void run(float (&d)[16], uint32_t dl) {
        KgenSteps<KS - 1>::run(d, dl);
        constexpr int k = KS - 1;
        wgmma_ss_n32<(k > 0), (O_H + (k / 4) * 3072 + (k % 4) * 32) / 16, (O_L + (k / 4) * 4096 + (k % 4) * 32) / 16>(d, dl);
    }
};
template <> struct KgenSteps<0> { static __device__ __forceinline__ void run(float (&)[16], uint32_t) {} };
template <int K0, int N, int I> struct NearSteps {
    static __device__ __forceinline__ void run(float (&d)[16], const uint4 (&f)[N], uint32_t dl) {
        NearSteps<K0, N, I - 1>::run(d, f, dl);
        constexpr int k = K0 + I - 1, dd = k / 4, kk = 4 * dd - (k - 3);
        wgmma_rs_n32<(O_U + (16 - dd) * 128 + kk * 32) / 16>(d, f[I - 1].x, f[I - 1].y, f[I - 1].z, f[I - 1].w, dl);
    }
};
template <int K0, int N> struct NearSteps<K0, N, 0> {
    static __device__ __forceinline__ void run(float (&)[16], const uint4 (&)[N], uint32_t) {}
};
template <int N>
__device__ __forceinline__ void load_toep(uint4 (&f)[N], uint32_t addr, uint32_t& prev) {
#pragma unroll
    for (int k = 0; k < N; k++)
    { const uint2 v = lds64(addr + k * 128); f[k].x = v.x; f[k].y = v.y; }
#pragma unroll
    for (int k = 0; k < N; k++) {
        f[k].z = prev;
        f[k].w = f[k].x;
        prev = f[k].y;
    }
}
__device__ __forceinline__ void mma16816(float (&d)[4], uint32_t a0, uint32_t a1, uint32_t a2, uint32_t b0,
                                         uint32_t b1) {
    asm("mma.sync.aligned.m16n8k16.row.col.f32.bf16.bf16.f32 {%0,%1,%2,%3}, {%4,%5,%6,%4}, {%7,%8}, {%0,%1,%2,%3};"
                 : "+f"(d[0]), "+f"(d[1]), "+f"(d[2]), "+f"(d[3])
                 : "r"(a0), "r"(a1), "r"(a2), "r"(b0), "r"(b1));
}
__device__ __forceinline__ uint4 ldsm_x4_t(uint32_t addr) {
    uint4 r;
    asm volatile("ldmatrix.sync.aligned.m8n8.x4.trans.shared.b16 {%0,%1,%2,%3}, [%4];"
                 : "=r"(r.x), "=r"(r.y), "=r"(r.z), "=r"(r.w) : "r"(addr));
    return r;
}
struct Params { const bf16 *A_re, *A_im, *B_re, *B_im, *C_re, *C_im, *log_dt, *Dskip; };
struct ModeIn { float ar, ai, br, bi, cr, ci, ldt, dsk; };
__device__ __forceinline__ ModeIn load_mode(const Params& p, int d, int n) {
    ModeIn m;
    const int i = d * N_MODES + n;
    m.ar = __bfloat162float(p.A_re[i]); m.ai = __bfloat162float(p.A_im[i]);
    m.br = __bfloat162float(p.B_re[i]); m.bi = __bfloat162float(p.B_im[i]);
    m.cr = __bfloat162float(p.C_re[i]); m.ci = __bfloat162float(p.C_im[i]);
    m.ldt = __bfloat162float(p.log_dt[d]); m.dsk = __bfloat162float(p.Dskip[d]);
    return m;
}

__device__ __forceinline__ void gen_powers(const ModeIn& mi, uint32_t sb, int t) {
    const float dt = bf16r(expf(mi.ldt));
    const float lr = dt * mi.ar, li = dt * mi.ai;
    const float br = dt * mi.br, bi = dt * mi.bi;
    cplx c;
    c.r = mi.cr * br - mi.ci * bi;
    c.i = mi.cr * bi + mi.ci * br;
    const cplx z = cexp_l(lr, li, 1.f), wv = cexp_l(lr, li, 8.f), Z = cexp_l(lr, li, 256.f);
    const cplx z2 = cmul(z, z), z4 = cmul(z2, z2);
    const uint32_t x0 = ((t & 31) >> 2) * 16 + (t & 3) * 4;
    uint32_t xs[8];
#pragma unroll
    for (int j = 0; j < 8; j++) xs[j] = sb + (x0 ^ (j << 4));
    const uint32_t ho = O_H + (t >> 5) * 3072, lo_ = O_L + (t >> 5) * 4096;
#define PUT_H(row, v) sts32(xs[(row) & 7] + ho + (row) * 128, pack_bf16((v).r, -(v).i))
#define PUT_L(row, v) sts32(xs[(row) & 7] + lo_ + (row) * 128, pack_bf16((v).r, (v).i))
    cplx h = c;
    PUT_H(0, h);
#pragma unroll
    for (int k = 1; k < 8; k++) { h = cmul(h, z); PUT_H(k, h); }
    cplx hz = cmul(c, Z);
    PUT_H(8, hz);
    { cplx a = cmul(hz, z2); PUT_H(9, a); a = cmul(hz, z4); PUT_H(10, a); a = cmul(a, z2); PUT_H(11, a); }
    hz = cmul(hz, Z); PUT_H(12, hz);
    { cplx a = cmul(hz, z4); PUT_H(13, a); }
    hz = cmul(hz, Z); PUT_H(14, hz);
    { cplx a = cmul(hz, z4); PUT_H(15, a); }
#pragma unroll
    for (int k = 16; k < 21; k++) { hz = cmul(hz, Z); PUT_H(k, hz); }
    const cplx w2 = cmul(wv, wv);
    cplx le, lo = wv;
    le.r = 1.f; le.i = 0.f;
    uint32_t lb = lo_;
#pragma unroll 1
    for (int kb = 0; kb < 4; kb++) {
#pragma unroll
        for (int k = 0; k < 8; k += 2) {
            sts32(xs[k] + lb + k * 128, pack_bf16(le.r, le.i));
            sts32(xs[k + 1] + lb + (k + 1) * 128, pack_bf16(lo.r, lo.i));
            le = cmul(le, w2); lo = cmul(lo, w2);
        }
        lb += 1024;
    }
}

__device__ __forceinline__ uint4 pack8(const float (&v)[8]) {
    return make_uint4(pack_bf16(v[0], v[1]), pack_bf16(v[2], v[3]), pack_bf16(v[4], v[5]), pack_bf16(v[6], v[7]));
}
__device__ __forceinline__ void st16B(uint32_t a, const uint4& v) { *sp<uint4>(a) = v; }

__device__ __forceinline__ void build_windows(uint32_t sb, int t) {
    if (t < 64) {
        const int which = t >> 4;
        sts128(sb + (which == 0 ? O_W1 : which == 1 ? O_W2 : which == 2 ? O_W3 : O_W4) - 256 + (t & 15) * 16, 0, 0, 0, 0);
    }
#pragma unroll
    for (int r = 0; r < 2; r++) {
        const int grp = t + r * 128;
        if (grp < 192) {
            const uint4 c0 = lds128(u_addr(sb, grp - 2)), c1 = lds128(u_addr(sb, grp - 1)), c2 = lds128(u_addr(sb, grp));
            float v[24];
            const uint32_t ww[12] = {c0.x, c0.y, c0.z, c0.w, c1.x, c1.y, c1.z, c1.w, c2.x, c2.y, c2.z, c2.w};
#pragma unroll
            for (int i = 2; i < 11; i++) { v[2 * i] = bf_lo(ww[i]); v[2 * i + 1] = bf_hi(ww[i]); }
            float p2[15];
#pragma unroll
            for (int j = 0; j < 15; j++) p2[j] = v[5 + j] + v[6 + j];
            float b1[8], b2[8];
#pragma unroll
            for (int i = 0; i < 8; i++) {
                b2[i] = p2[i + 6] + v[13 + i];
                b1[i] = p2[i + 1] + p2[i + 3] + v[10 + i];
            }
            st16B(sb + O_W1 + grp * 16, pack8(b1));
            st16B(sb + O_W2 + grp * 16, pack8(b2));
            if (r == 0) {
                float b3[8], b5[8];
#pragma unroll
                for (int i = 0; i < 8; i++) {
                    b3[i] = b1[i] + v[11 + i] + v[5 + i];
                    b5[i] = p2[i + 7];
                }
                st16B(sb + O_W3 + grp * 16, pack8(b3));
                st16B(sb + O_W5 + grp * 16, pack8(b5));
                st16B(sb + O_W4 + grp * 16, make_uint4(hadd2_bf(ww[6], ww[2]), hadd2_bf(ww[7], ww[3]),
                                                       hadd2_bf(ww[8], ww[4]), hadd2_bf(ww[9], ww[5])));
            }
        }
    }
}

__device__ __forceinline__ void build_tables(float (&kd)[16], float dskip, uint32_t sb, int t, int bar) {
    const int lane = t & 31, w = t >> 5, g = lane >> 2, tq = lane & 3;
    if (w == 0) {
        if (lane == 0) kd[0] += dskip;
        const uint32_t kn = sb + O_KN + 128;
#pragma unroll
        for (int j = 0; j < 4; j++) {
            const int lo = 8 * j + 2 * tq;
            const uint32_t p0 = pack_bf16(kd[4 * j], kd[4 * j + 1]), p1 = pack_bf16(kd[4 * j + 2], kd[4 * j + 3]);
            sts16(kn + (g + 8 * lo) * 2, p0);
            sts16(kn + (g + 8 * lo + 8) * 2, p0 >> 16);
            if (g < 4) {
#pragma unroll
                for (int e = 0; e < 2; e++) {
                    const uint32_t val = e ? (p1 >> 16) : p1, ad = kn + (256 + 2 * g + 8 * (lo + e)) * 2;
                    sts16(ad, val);
                    if (!(g & 1)) {
                        sts16(ad + 2, val);
                        if (g + lo + e > 0) sts16(ad - 2, val);
                    }
                }
            } else {
#pragma unroll
                for (int e = 0; e < 2; e++) {
                    const uint32_t val = e ? (p1 >> 16) : p1;
                    const int i8 = 64 + (g >= 6 ? 32 : 0) + lo + e;
                    if (j > 0 || i8 >= 66) {
                        sts16(sb + O_A12 + (i8 - 48) * 4 - ((g & 1) ? 0 : 2), val);
                    } else if (g & 1) {
                        sts16(kn + (8 * i8 + 3) * 2, val); sts16(kn + (8 * i8 + 4) * 2, val); sts16(kn + (8 * i8 + 5) * 2, val);
                    } else {
#pragma unroll
                        for (int dd = -2; dd <= 2; dd++)
                            if (i8 == 65 || dd >= -1) sts16(kn + (8 * i8 + dd) * 2, val);
                    }
                }
            }
        }
    } else if (w == 1) {
        if (g < 4) {
#pragma unroll
            for (int j = 0; j < 4; j++) {
                const int i8 = 128 + 32 * g + 8 * j + 2 * tq;
                const uint32_t p0 = pack_bf16(kd[4 * j], kd[4 * j + 1]);
                if (i8 == 128) { sts16(sb + O_A12 + (127 - 48) * 4 + 2, p0); sts16(sb + O_KQ, p0); }
                else sts16(sb + O_A3 + (i8 - 1 - 112) * 2, p0);
                sts16(sb + O_A3 + (i8 - 112) * 2, p0 >> 16);
            }
        } else if (lane == 16) {
            sts16(sb + O_A3 + (255 - 112) * 2, pack_bf16(kd[0], 0.f));
        }
    }
    wg_bar(bar);
    DBG1(4);
    {
#pragma unroll
        for (int r = 0; r < 2; r++) {
            const int i = t + r * 128;
            if (i < 160) {
                const uint32_t ka = sb + O_KN + (4 * i + 8) * 2;
                const uint32_t wm = lds32(ka - 4), w3 = lds32(ka + 12);
                const uint2 wa = lds64(ka), wb = lds64(ka + 16);
                const uint32_t w0 = wa.x, w1 = wa.y, w4 = wb.x, w5 = wb.y;
                sts128(sb + O_Q + i * 32, __byte_perm(w0, wm, 0x7610), __byte_perm(w4, w3, 0x7610),
                       __byte_perm(w0, w0, 0x1032), __byte_perm(w4, w4, 0x1032));
                sts128(sb + O_Q + i * 32 + 16, __byte_perm(w1, w0, 0x7610), __byte_perm(w5, w4, 0x7610),
                       __byte_perm(w1, w1, 0x1032), __byte_perm(w5, w5, 0x1032));
            }
        }
        {
            const uint32_t aa = sb + O_A3 + (8 + t) * 2;
            const uint32_t p0 = lds16(aa) | (lds16(aa - 2) << 16), p1 = lds16(aa + 16) | (lds16(aa + 14) << 16);
            const uint32_t msk = (t & 1) ? 0x0000ffffu : 0xffff0000u;
            sts128(sb + O_Q34 + t * 16, p0, p1, p0 & msk, p1 & msk);
        }
        if (t >= 48) {
            const uint32_t aa = sb + O_A12 + (t - 48 + 8) * 4;
            const uint32_t e0 = lds32(aa), e1 = lds32(aa - 4), f0 = lds32(aa + 32), f1 = lds32(aa + 28);
            sts128(sb + O_Q12 + (t - 48) * 16, __byte_perm(e0, e1, 0x7632), __byte_perm(f0, f1, 0x7632),
                   __byte_perm(e0, e1, 0x5410), __byte_perm(f0, f1, 0x5410));
        }
    }
}

__device__ __forceinline__ void convolve(int d, uint32_t sb, int t, int bar, const CUtensorMap* tmo) {
    const int lane = t & 31, w = t >> 5, g = lane >> 2, tq = lane & 3;
    const uint32_t dl = (sb & 0x3FFFF) >> 4;
    float y[16];
#pragma unroll
    for (int i = 0; i < 16; i++) y[i] = 0.f;
    {
        const uint32_t qa = sb + O_Q + (16 * w + g - 2 * tq + 56 - 48) * 8;
        uint32_t prev = 0;
        uint32_t qp = qa, du = dl;
#pragma unroll 1
        for (int jj = 0; jj < 4; jj++) {
            uint4 F[8];
            load_toep<8>(F, qp, prev);
            WG_FENCE();
            NearSteps<0, 8, 8>::run(y, F, du);
            WG_COMMIT();
            WG_WAIT(0);
            qp += 8 * 128;
            du -= 16;
        }
        uint4 FC[5];
        load_toep<5>(FC, qp, prev);
        WG_FENCE();
        NearSteps<0, 5, 5>::run(y, FC, du);
        WG_COMMIT();
        WG_WAIT(0);
#pragma unroll
        for (int i = 0; i < 16; i++) asm volatile("" : "+f"(y[i])::"memory");
    }
    DBG1(6);
    {
        const int par = w & 1;
        const uint32_t qoff = sb + (g - 2 * tq) * 16;
        const uint32_t roff = sb + (lane & 15) * 16 + par * 256;
        const uint32_t yoff = sb + (136 * par + 8 * g + 2 * tq) * 4;
        if (w < 2) {
            const uint32_t wb = roff + ((lane >> 4) ? O_W2 : O_W1);
            uint4 f[5];
#pragma unroll
            for (int q = 4; q <= 8; q++) f[q - 4] = lds128(qoff + O_Q12 + (16 * q - 56) * 16);
            uint4 bt[12];
#pragma unroll
            for (int i = 0; i < 6; i++) {
                if (i == 0) bt[0] = ldsm_x4_t(wb - 256);
                bt[2 * i + 1] = ldsm_x4_t(wb + (2 * i) * 256);
                if (i > 0) bt[2 * i] = ldsm_x4_t(wb + (2 * i - 1) * 256);
                float a0[4] = {0.f, 0.f, 0.f, 0.f}, a1[4] = {0.f, 0.f, 0.f, 0.f};
#pragma unroll
                for (int q = 4; q <= 8; q++) {
                    const int k = 2 * i + 4 - q;
                    if (k >= -1) {
                        mma16816(a0, f[q - 4].x, f[q - 4].y, q > 4 ? f[q > 4 ? q - 5 : 0].y : 0u, bt[k + 1].x, bt[k + 1].y);
                        mma16816(a1, f[q - 4].z, f[q - 4].w, q > 4 ? f[q > 4 ? q - 5 : 0].w : 0u, bt[k + 1].z, bt[k + 1].w);
                    }
                }
                const uint32_t ya = yoff + O_Y12 + 136 * (4 + 2 * i) * 4;
                sts64f(ya, a0[0] + a1[0], a0[1] + a1[1]);
                sts64f(ya + 256, a0[2] + a1[2], a0[3] + a1[3]);
            }
        } else {
            const uint32_t wb = roff + ((lane >> 4) ? O_W4 : O_W3);
            uint4 bt[8];
#pragma unroll
            for (int k = 0; k < 8; k++) bt[k] = ldsm_x4_t(wb + (k - 1) * 256);
            const uint4 b5a = ldsm_x4_t(roff + O_W5 + (lane >> 4) * 512), b5b = ldsm_x4_t(roff + O_W5 + 1024 + (lane >> 4) * 512);
            const uint32_t kq = lds16(sb + O_KQ);
            const uint32_t dg = (g == 2 * tq) ? kq : ((g == 2 * tq + 1) ? (kq << 16) : 0u);
            float acc[4][4];
#pragma unroll
            for (int i = 0; i < 4; i++)
#pragma unroll
                for (int j = 0; j < 4; j++) acc[i][j] = 0.f;
            mma16816(acc[0], dg, 0u, 0u, b5a.x, b5a.y);
            mma16816(acc[1], dg, 0u, 0u, b5a.z, b5a.w);
            mma16816(acc[2], dg, 0u, 0u, b5b.x, b5b.y);
            mma16816(acc[3], dg, 0u, 0u, b5b.z, b5b.w);
            uint32_t pa = 0, pb = 0;
#pragma unroll
            for (int q = 8; q <= 15; q++) {
                const uint4 f = lds128(qoff + O_Q34 + (16 * q - 120) * 16);
#pragma unroll
                for (int i = 0; i < 4; i++) {
                    const int k = 2 * i + 8 - q;
                    if (k >= -1) mma16816(acc[i], f.x, f.y, pa, bt[k + 1].x, bt[k + 1].y);
                }
#pragma unroll
                for (int i = 0; i < 4; i++) {
                    const int k = 2 * i + 8 - q;
                    if (k >= -1) mma16816(acc[i], f.z, f.w, pb, bt[k + 1].z, bt[k + 1].w);
                }
                pa = f.y; pb = f.w;
            }
#pragma unroll
            for (int i = 0; i < 4; i++) {
                const uint32_t ya = yoff + O_Y34 + 136 * (8 + 2 * i) * 4;
                sts64f(ya, acc[i][0], acc[i][1]);
                sts64f(ya + 256, acc[i][2], acc[i][3]);
            }
        }
    }
    wg_bar(bar);
    DBG1(7);
    {
        const uint32_t yb = sb + (136 * tq + 16 * w + g) * 4;
#pragma unroll
        for (int j = 1; j < 4; j++)
#pragma unroll
            for (int e = 0; e < 4; e++) {
                const uint32_t o = yb + (544 * j + 64 * (e & 1) + 8 * (e >> 1)) * 4;
                y[4 * j + e] += ldsf(o + O_Y12);
                if (j >= 2) y[4 * j + e] += ldsf(o + O_Y34);
            }
#pragma unroll
        for (int jp = 0; jp < 2; jp++) {
            const int a = 8 * (2 * jp + (lane >> 4)) + (lane & 7);
            const uint32_t addr = sb + O_ST + a * 128 + (((2 * w + ((lane >> 3) & 1)) ^ (lane & 7)) << 4);
            asm volatile("stmatrix.sync.aligned.m8n8.x4.trans.shared.b16 [%0], {%1,%2,%3,%4};" ::"r"(addr),
                         "r"(pack_bf16(y[8 * jp + 0], y[8 * jp + 1])), "r"(pack_bf16(y[8 * jp + 2], y[8 * jp + 3])),
                         "r"(pack_bf16(y[8 * jp + 4], y[8 * jp + 5])), "r"(pack_bf16(y[8 * jp + 6], y[8 * jp + 7]))
                         : "memory");
        }
        asm volatile("fence.proxy.async.shared::cta;" ::: "memory");
        wg_bar(bar);
        if (t == 0) {
            asm volatile("cp.async.bulk.tensor.2d.global.shared::cta.bulk_group [%0, {%1, %2}], [%3];"
                         ::"l"(tmo), "r"(0), "r"(d * 32), "r"(sb + O_ST) : "memory");
            asm volatile("cp.async.bulk.commit_group;" ::: "memory");
            asm volatile("cp.async.bulk.wait_group.read 0;" ::: "memory");
        }
        DBG1(8);
    }
}

constexpr int K1_WGS = 5;
constexpr int O_XTRA = K1_WGS * WG_BYTES;
constexpr int K1_SMEM = O_XTRA + 3 * 4096;
constexpr int K1_CTAS = (D_MODEL + K1_WGS - 1) / K1_WGS;
constexpr int K1_STAT = 16;
__device__ __forceinline__ uint32_t raw_box(uint32_t sbase, int i) {
    return i < K1_WGS ? sbase + i * WG_BYTES + O_RAW : sbase + O_XTRA + (i - K1_WGS) * 4096;
}
__device__ __forceinline__ void transpose_window(uint32_t sbase, int warp, int lane, int ch0) {
    const int ch = (lane >> 2) + ch0;
    const uint32_t ub = sbase + ch * WG_BYTES + (lane & 3) * 4;
#pragma unroll
    for (int k = 0; k < 4; k++) {
        const int gi = warp + k * (4 * K1_WGS);
        if (gi < 64) {
            const uint4 v = ldsm_x4_t(raw_box(sbase, gi >> 3) + (gi & 7) * 512 + lane * 16);
            if (ch >= 0 && ch < K1_WGS) {
                const uint32_t a0 = u_addr(ub, 4 * gi);
                sts32(a0, v.x);
                sts32(a0 ^ 16, v.y);
                sts32(a0 ^ 32, v.z);
                sts32(a0 ^ 48, v.w);
            }
        }
    }
}

__global__ void __launch_bounds__(128 * K1_WGS, 1)
ssm_kernel(const __grid_constant__ CUtensorMap tmc, const __grid_constant__ CUtensorMap tmo,
           const bf16* __restrict__ x, const bf16* __restrict__ gw, Params p) {
    extern __shared__ __align__(1024) uint8_t smem_raw[];
    const uint32_t sbase = smem_u32(smem_raw);
    const int tid = threadIdx.x, t = tid & 127, lane = tid & 31;
    const int wg = __shfl_sync(0xffffffffu, tid >> 7, 0), warp = __shfl_sync(0xffffffffu, tid >> 5, 0);
    const int d0 = blockIdx.x * K1_WGS, d = min(d0 + wg, D_MODEL - 1);
    const uint32_t sb = sbase + wg * WG_BYTES;
    const uint32_t xbar = sbase + WG_BYTES - 16;
    const int dw = d0 & ~7;
    const bool two = (d0 & 7) > 3 && dw + 8 < D_MODEL;
    DBG1(0);
    if (blockIdx.x == 0) {
        if (tid == 0) {
            g_epoch = g_epoch + 1;
            asm volatile("fence.acq_rel.gpu;" ::: "memory");
        }
        __syncthreads();
    }
    asm volatile("griddepcontrol.launch_dependents;");
    if (blockIdx.x >= K1_CTAS) {
        const uint32_t tag = (g_stat_epoch[blockIdx.x - K1_CTAS] + 1) & 1u;
        __syncthreads();
        if (tid == 0) g_stat_epoch[blockIdx.x - K1_CTAS] = g_stat_epoch[blockIdx.x - K1_CTAS] + 1;
        uint32_t gr[9];
#pragma unroll
        for (int i = 0; i < 9; i++) gr[i] = __ldg(reinterpret_cast<const uint32_t*>(gw) + lane + 32 * i);
#pragma unroll 1
        for (int row = (blockIdx.x - K1_CTAS) * (4 * K1_WGS) + warp; row < L_SEQ; row += 2 * K1_STAT * 4 * K1_WGS) {
            const int row2 = min(row + K1_STAT * 4 * K1_WGS, L_SEQ - 1);
            uint32_t xr[2][9];
#pragma unroll
            for (int i = 0; i < 9; i++) {
                xr[0][i] = __ldg(reinterpret_cast<const uint32_t*>(x + (size_t)row * D_MODEL) + lane + 32 * i);
                xr[1][i] = __ldg(reinterpret_cast<const uint32_t*>(x + (size_t)row2 * D_MODEL) + lane + 32 * i);
            }
#pragma unroll
            for (int h = 0; h < 2; h++) {
                float s = 0.f, gs = 0.f;
#pragma unroll
                for (int i = 0; i < 9; i++) {
                    s += bf_lo(xr[h][i]) + bf_hi(xr[h][i]);
                    const uint32_t pr = hmul2_bf(xr[h][i], gr[i]);
                    gs += bf_lo(pr) + bf_hi(pr);
                }
#pragma unroll
                for (int o = 16; o; o >>= 1) {
                    s += __shfl_xor_sync(~0u, s, o);
                    gs += __shfl_xor_sync(~0u, gs, o);
                }
                const float mean = s * (1.f / D_MODEL);
                float q = 0.f;
#pragma unroll
                for (int i = 0; i < 9; i++) {
                    const float a = bf_lo(xr[h][i]) - mean, b = bf_hi(xr[h][i]) - mean;
                    q = fmaf(a, a, fmaf(b, b, q));
                }
#pragma unroll
                for (int o = 16; o; o >>= 1) q += __shfl_xor_sync(~0u, q, o);
                if (lane == 0) {
                    const float var = bf16r(q * (1.f / D_MODEL));
                    const float den = bf16r(sqrtf(bf16r(var + 1e-5f)));
                    const int r = h ? row2 : row;
                    const unsigned long long e = ((unsigned long long)((__float_as_uint(__fdividef(1.f, den)) & ~1u) | tag) << 32) |
                                                 pack_bf16(mean, mean);
                    asm volatile("st.relaxed.gpu.global.b64 [%0], %1;" ::"l"(&g_rowstat[r]), "l"(e) : "memory");
                    g_gate[r] = bf16r(__fdividef(1.f, 1.f + __expf(-bf16r(gs))));
                }
            }
        }
        return;
    }
    if (tid == 0) {
        mbar_init(xbar, 1);
        asm volatile("fence.mbarrier_init.release.cluster;" ::: "memory");
        mbar_expect(xbar, 8 * 4096);
#pragma unroll
        for (int i = 0; i < 8; i++) tma2d(raw_box(sbase, i), &tmc, dw, i * 256, xbar);
    }
    const ModeIn mi = load_mode(p, d, t);
    sts128(sb + O_U + t * 16, 0, 0, 0, 0);
    sts128(sb + O_KN + t * 16, 0, 0, 0, 0);
    gen_powers(mi, sb, t);
    DBG1(1);
    asm volatile("fence.proxy.async.shared::cta;" ::: "memory");
    __syncthreads();
    float kd[16];
    WG_FENCE();
    KgenSteps<16>::run(kd, (sb & 0x3FFFF) >> 4);
    WG_COMMIT();
    mbar_wait(xbar, 0);
    DBG1(2);
    transpose_window(sbase, warp, lane, dw - d0);
    if (two) {
        asm volatile("fence.proxy.async.shared::cta;" ::: "memory");
        __syncthreads();
        if (tid == 0) {
            mbar_expect(xbar, 8 * 4096);
#pragma unroll
            for (int i = 0; i < 8; i++) tma2d(raw_box(sbase, i), &tmc, dw + 8, i * 256, xbar);
        }
    }
    DBG1(3);
    WG_WAIT(0);
#pragma unroll
    for (int i = 0; i < 16; i++) asm volatile("" : "+f"(kd[i])::"memory");
    build_tables(kd, mi.dsk, sb, t, 1 + wg);
    if (two) {
        mbar_wait(xbar, 1);
        transpose_window(sbase, warp, lane, dw + 8 - d0);
    }
    asm volatile("fence.proxy.async.shared::cta;" ::: "memory");
    __syncthreads();
    DBG1(5);
    build_windows(sb, t);
    wg_bar(1 + wg);
    DBG1(9);
    if (d0 + wg < D_MODEL) convolve(d, sb, t, 1 + wg, &tmo);
}
}

constexpr int XT_BYTES = 128 * D_MODEL * 2;
constexpr int STAGE_BYTES = 96 * 128;
constexpr int NSTAGE = 6;
constexpr int SM_STAGES = XT_BYTES;
constexpr int SM_BARS = SM_STAGES + NSTAGE * STAGE_BYTES;
constexpr int SM_B1 = SM_BARS + 512;
constexpr int SM_B2 = SM_B1 + 576 * 4;
constexpr int MLP_SMEM = SM_B2 + 576 * 2;
__host__ __device__ constexpr int red_buf(int c) { return c < 7 ? c * 18432 : SM_STAGES + (c - 7) * 18432; }
constexpr int BAR_FULL = 0, BAR_EMPTY = 48, BAR_X = 96, BAR_PARKFREE = 168, BAR_STORED = 176, BAR_LOADED = 248, BAR_A = 320;

__device__ __forceinline__ float gelu2(float x) {
    const float k0 = 0.7978845608028654f, k1 = 0.7978845608028654f * 0.044715f;
    float u = x * fmaf(x * x, k1, k0);
    float th;
    asm("tanh.approx.f32 %0, %1;" : "=f"(th) : "f"(u));
    return fmaf(x, th, x);
}

__device__ __forceinline__ void epi_gelu(const float (&acc)[32], int i, uint32_t b1_addr, float r0, float r1,
                                         uint32_t (&o)[4]) {
    float b0, b1, b2, b3;
    asm volatile("ld.shared.v4.f32 {%0,%1,%2,%3}, [%4];"
                 : "=f"(b0), "=f"(b1), "=f"(b2), "=f"(b3) : "r"(b1_addr + i * 16));
    o[0] = pack_bf16(gelu2(fmaf(acc[8 * i + 0], r0, b0)), gelu2(fmaf(acc[8 * i + 1], r0, b1)));
    o[1] = pack_bf16(gelu2(fmaf(acc[8 * i + 2], r1, b0)), gelu2(fmaf(acc[8 * i + 3], r1, b1)));
    o[2] = pack_bf16(gelu2(fmaf(acc[8 * i + 4], r0, b2)), gelu2(fmaf(acc[8 * i + 5], r0, b3)));
    o[3] = pack_bf16(gelu2(fmaf(acc[8 * i + 6], r1, b2)), gelu2(fmaf(acc[8 * i + 7], r1, b3)));
}
__device__ __forceinline__ void epi_park(const float (&acc)[32], int i, uint32_t b1_addr, uint32_t park_addr,
                                         float r0, float r1) {
    uint32_t o[4];
    epi_gelu(acc, i, b1_addr, r0, r1, o);
    asm volatile("st.shared.v4.b32 [%0], {%1,%2,%3,%4};" ::"r"(park_addr + i * 4096), "r"(o[0]), "r"(o[1]),
                 "r"(o[2]), "r"(o[3]) : "memory");
}
__device__ __forceinline__ void epi_part(const float (&acc)[32], int i, uint4* part, uint32_t par) {
    uint4 v;
    v.x = (pack_bf16(acc[8 * i + 0], acc[8 * i + 1]) & ~1u) | par;
    v.y = pack_bf16(acc[8 * i + 2], acc[8 * i + 3]);
    v.z = (pack_bf16(acc[8 * i + 4], acc[8 * i + 5]) & ~1u) | par;
    v.w = pack_bf16(acc[8 * i + 6], acc[8 * i + 7]);
    asm volatile("{\n.reg .b128 q;\nmov.b128 q, {%1, %2};\nst.relaxed.gpu.global.b128 [%0], q;\n}\n" ::"l"(part + i * 32),
                 "l"(((unsigned long long)v.y << 32) | v.x), "l"(((unsigned long long)v.w << 32) | v.z) : "memory");
}
__device__ __forceinline__ void warp_arrive(uint32_t bar, int lane) {
    __syncwarp();
    if (lane == 0) asm volatile("mbarrier.arrive.shared::cta.b64 _, [%0];" ::"r"(bar) : "memory");
}

__device__ __forceinline__ void probe_partials(const uint4* unit, uint32_t par) {
    asm volatile(
        "{\n.reg .pred p;\n.reg .u32 n, v;\nmov.u32 n, 0;\n"
        "PROBE_LOOP:\n"
        "ld.relaxed.gpu.global.u32 v, [%0];\n"
        "xor.b32 v, v, %1;\n"
        "and.b32 v, v, 1;\n"
        "setp.ne.u32 p, v, 0;\n"
        "vote.sync.any.pred p, p, 0xffffffff;\n"
        "@!p bra PROBE_DONE;\n"
        "add.u32 n, n, 1;\n"
        "setp.lt.u32 p, n, 1048576;\n"
        "@p bra PROBE_LOOP;\n"
        "trap;\n"
        "PROBE_DONE:\n}\n" ::"l"(unit), "r"(par) : "memory");
}

template <int EPI>
__device__ __forceinline__ void run_chunk(float (&cur)[32], float (&prev)[32], const uint32_t (&af)[NAF][4],
                                          int parity, uint32_t bars, uint32_t desc0, uint32_t adesc0, uint32_t p0, uint32_t p1,
                                          uint4* part, bool sig, uint32_t rbar, int lane, float r0, float r1) {
#pragma unroll
    for (int s = 0; s < 6; s++) {
        mbar_wait(bars + BAR_FULL + s * 8, parity);
        WG_FENCE();
        mma_stage_rt(s, cur, af, desc0, adesc0);
        WG_COMMIT();
        if (s >= 1 && s <= 4) {
            if (EPI == 1) epi_park(prev, s - 1, p0, p1, r0, r1);
            if (EPI == 2) epi_part(prev, s - 1, part, p1);
        }
        if (s == 4 && EPI == 2) warp_arrive(p0, lane);
        WG_WAIT(1);
        if (sig) asm volatile("mbarrier.arrive.shared::cluster.b64 _, [%0];" ::"r"(rbar + ((s + 5) % 6) * 8) : "memory");
        if (s == 0) fence_acc(prev);
    }
}

__global__ void __cluster_dims__(2, 1, 1) __launch_bounds__(384, 1)
mlp_kernel(const __grid_constant__ CUtensorMap tmx, const __grid_constant__ CUtensorMap tmw1,
           const __grid_constant__ CUtensorMap tmw2, const __grid_constant__ CUtensorMap tma,
           const bf16* __restrict__ b1, const bf16* __restrict__ b2,
           bf16* __restrict__ out) {
    extern __shared__ __align__(1024) uint8_t smem_raw[];
    const uint32_t sbase = smem_u32(smem_raw);
    uint8_t* sgen = smem_raw;
    const int tid = threadIdx.x, lane = tid & 31;
    const int warp = __shfl_sync(0xffffffffu, tid >> 5, 0);
    const int wgid = __shfl_sync(0xffffffffu, tid >> 7, 0);
    const int m = blockIdx.x & 15, f = blockIdx.x >> 4;
    const uint32_t rank = m & 1;
    const uint32_t bars = sbase + SM_BARS;
    if (warp == 0) DBG(12);

    if (tid == 0) {
        if (sbase & 1023) asm volatile("trap;");
        for (int i = 0; i < NSTAGE; i++) {
            mbar_init(bars + BAR_FULL + i * 8, 1);
            mbar_init(bars + BAR_EMPTY + i * 8, 4);
        }
        for (int i = 0; i < 9; i++) mbar_init(bars + BAR_X + i * 8, 1);
        mbar_init(bars + BAR_PARKFREE, 8);
        mbar_init(bars + BAR_A, 1);
        for (int i = 0; i < 9; i++) {
            mbar_init(bars + BAR_STORED + i * 8, 8);
            mbar_init(bars + BAR_LOADED + i * 8, 1);
        }
        asm volatile("fence.mbarrier_init.release.cluster;" ::: "memory");
        for (int j = 0; j < 3; j++) {
            mbar_expect(bars + BAR_X + j * 8, 16384);
            tma2d(sbase + j * 16384, &tmx, j * 64, m * 128, bars + BAR_X + j * 8);
        }
    }
    uint32_t b1v0 = 0, b1v1 = 0;
    if (wgid < 2) {
        const uint32_t* b1w = reinterpret_cast<const uint32_t*>(b1 + f * 576);
        b1v0 = __ldg(b1w + (tid >> 5) * 32 + (tid & 7) * 4 + ((tid >> 3) & 3));
        if (tid < 32) b1v1 = __ldg(b1w + 8 * 32 + (tid & 7) * 4 + ((tid >> 3) & 3));
    }
    __syncthreads();
    asm volatile("barrier.cluster.arrive.relaxed.aligned;\nbarrier.cluster.wait.aligned;" ::: "memory");

    if (warp == 0) DBG(0);
    if (wgid == 2) {
        asm volatile("setmaxnreg.dec.sync.aligned.u32 40;");
        if (warp == 8) {
            if (lane == 0) {
                const uint32_t dst0 = sbase + SM_STAGES + rank * (STAGE_BYTES / 2);
#pragma unroll 1
                for (int cc = 0; cc < 18; cc++) {
                    const CUtensorMap* tm = cc < 9 ? &tmw1 : &tmw2;
                    const int c0 = cc < 9 ? f * 576 + cc * 64 : (cc - 9) * 64;
                    const int c1 = (cc < 9 ? 0 : f * 576) + rank * 48;
                    const int par = (cc & 1) ^ 1;
#pragma unroll
                    for (int s = 0; s < 6; s++) {
                        mbar_wait(bars + BAR_EMPTY + s * 8, par);
                        mbar_expect(bars + BAR_FULL + s * 8, STAGE_BYTES);
                        tma2d_mc(dst0 + s * STAGE_BYTES, tm, c0, c1 + s * 96, bars + BAR_FULL + s * 8, 3);
                        if (cc == 0 && s >= 1 && s <= 3) {
#pragma unroll
                            for (int j = 2 * s + 1; j < 2 * s + 3; j++) {
                                mbar_expect(bars + BAR_X + j * 8, 16384);
                                tma2d(sbase + j * 16384, &tmx, j * 64, m * 128, bars + BAR_X + j * 8);
                            }
                        }
                    }
                }
            }
        } else if (warp == 9) {
            {
                uint32_t* b2s = reinterpret_cast<uint32_t*>(sgen + SM_B2);
                for (int w = lane; w < 288; w += 32) {
                    const int jj = w & 1, q = (w >> 1) & 3, ci = w >> 3;
                    b2s[w] = __ldg(reinterpret_cast<const uint32_t*>(b2) + ci * 8 + jj * 4 + q);
                }
                __syncwarp();
            }
            asm volatile("griddepcontrol.wait;" ::: "memory");
            const uint32_t par = __ldcg(&g_epoch);
            mbar_wait(bars + BAR_PARKFREE, 0);
            asm volatile("fence.proxy.async.shared::cta;" ::: "memory");
            const uint4* psrc = g_part + (m * 9 * 8 + f) * (8 * 4 * 32);
#pragma unroll 1
            for (int c = 0; c < 9; c++) {
                const uint32_t buf = sbase + red_buf(c);
                if (c == 7) {
                    mbar_wait(bars + BAR_EMPTY + 0, 1);
                    mbar_wait(bars + BAR_EMPTY + 8, 1);
                    mbar_wait(bars + BAR_EMPTY + 16, 1);
                }
                if (lane == 0) {
                    mbar_expect(bars + BAR_LOADED + c * 8, 16384 + 2048);
                    tma2d(buf + 16384, &tma, m * 128 + f * 16, c * 64, bars + BAR_LOADED + c * 8);
                }
                mbar_wait(bars + BAR_STORED + c * 8, 0);
                probe_partials(psrc + (lane & 7) * 128 + 96 + 31, par);
                DBG(16 + c);
                if (lane == 0)
                    asm volatile("cp.async.bulk.shared::cluster.global.mbarrier::complete_tx::bytes [%0], [%1], 16384, [%2];"
                                 ::"r"(buf), "l"(psrc), "r"(bars + BAR_LOADED + c * 8) : "memory");
                psrc += 8 * 8 * 4 * 32;
            }
        }
        __syncwarp();
        asm volatile("barrier.cluster.arrive.release.aligned;\nbarrier.cluster.wait.acquire.aligned;" ::: "memory");
    } else {
        asm volatile("setmaxnreg.inc.sync.aligned.u32 232;");
        const uint32_t par = __ldcg(&g_epoch) & 1u;
        uint2 rs0, rs1;
        {
            const uint2* rp = &g_rowstat[m * 128 + warp * 16 + (lane >> 2)];
            int tries = 0;
            while (true) {
                unsigned long long e0, e1;
                asm volatile("ld.relaxed.gpu.global.b64 %0, [%1];" : "=l"(e0) : "l"(rp) : "memory");
                asm volatile("ld.relaxed.gpu.global.b64 %0, [%1];" : "=l"(e1) : "l"(rp + 8) : "memory");
                rs0 = make_uint2((uint32_t)e0, (uint32_t)(e0 >> 32));
                rs1 = make_uint2((uint32_t)e1, (uint32_t)(e1 >> 32));
                if (!__any_sync(0xffffffffu, ((rs0.y ^ par) | (rs1.y ^ par)) & 1)) break;
                if (++tries > (1 << 22)) asm volatile("trap;");
            }
        }
        const int g = lane >> 2, tq = lane & 3;
        uint32_t af[NAF][4];
        float acc0[32], acc1[32];
        const bool sig = (tid & 127) < 2;
        uint32_t rbar;
        asm volatile("mapa.shared::cluster.u32 %0, %1, %2;" : "=r"(rbar) : "r"(bars + BAR_EMPTY), "r"(tid & 1));
        const uint32_t desc0 = ((sbase + SM_STAGES) & 0x3FFFF) >> 4;
        const uint32_t adesc0 = ((sbase + 8 * 16384 + wgid * 8192) & 0x3FFFF) >> 4;

        {
            float2* b1s = reinterpret_cast<float2*>(sgen + SM_B1);
            b1s[tid] = make_float2(bf_lo(b1v0), bf_hi(b1v0));
            if (tid < 32) b1s[256 + tid] = make_float2(bf_lo(b1v1), bf_hi(b1v1));
        }
        const float rstd0 = __uint_as_float(rs0.y), rstd1 = __uint_as_float(rs1.y);
        {
            const int lrow = warp * 16 + (lane & 7) + ((lane >> 3) & 1) * 8;
            const uint32_t rbase = sbase + lrow * 128;
            const int hi = lane >> 4, sw = lrow & 7;
#pragma unroll
            for (int s = 0; s < 6; s++) {
#pragma unroll
                for (int k = s * 6; k < s * 6 + 6; k++) {
                    const int j = k >> 2, kk = k & 3;
                    if (kk == 0 || k == s * 6) mbar_wait(bars + BAR_X + j * 8, 0);
                    uint32_t tmp[4];
                    uint32_t (&a)[4] = (k < NAF) ? af[(k < NAF) ? k : 0] : tmp;
                    const uint32_t addr = rbase + j * 16384 + (((kk * 2 + hi) ^ sw) << 4);
                    ldsm_x4(a, addr);
                    a[0] = hsub2_bf(a[0], rs0.x);
                    a[1] = hsub2_bf(a[1], rs1.x);
                    a[2] = hsub2_bf(a[2], rs0.x);
                    a[3] = hsub2_bf(a[3], rs1.x);
                    if (k >= NAF) stsm_x4(a, addr);
                }
                if (s == 5) {
                    asm volatile("fence.proxy.async.shared::cta;" ::: "memory");
                    asm volatile("bar.sync %0, 128;" ::"r"(3 + wgid) : "memory");
                    if (warp == 0) DBG(1);
                }
                mbar_wait(bars + BAR_FULL + s * 8, 0);
                WG_FENCE();
                mma_stage_rt(s, acc0, af, desc0, adesc0);
                WG_COMMIT();
                if (s > 0) {
                    WG_WAIT(1);
                    if (sig) asm volatile("mbarrier.arrive.shared::cluster.b64 _, [%0];" ::"r"(rbar + (s - 1) * 8) : "memory");
                }
            }
            asm volatile("bar.sync 1, 256;" ::: "memory");
        }
        {
            uint32_t b1a = sbase + SM_B1 + tq * 64, park = sbase + tid * 16;
#pragma unroll 1
            for (int c = 1; c < 9; c += 2) {
                if (warp == 0) DBG(2 + (c >> 1));
                run_chunk<1>(acc1, acc0, af, 1, bars, desc0, adesc0, b1a, park, nullptr, sig, rbar, lane, rstd0, rstd1);
                run_chunk<1>(acc0, acc1, af, 0, bars, desc0, adesc0, b1a + 256, park + 16384, nullptr, sig, rbar, lane, rstd0, rstd1);
                b1a += 512;
                park += 32768;
            }
        }
        if (warp == 0) DBG(6);
        WG_WAIT(0);
        if (sig) asm volatile("mbarrier.arrive.shared::cluster.b64 _, [%0];" ::"r"(rbar + 5 * 8) : "memory");
        fence_acc(acc0);
#pragma unroll
        for (int k = 0; k < 32; k++)
            asm volatile("ld.shared.v4.b32 {%0,%1,%2,%3}, [%4];"
                         : "=r"(af[k][0]), "=r"(af[k][1]), "=r"(af[k][2]), "=r"(af[k][3])
                         : "r"(sbase + tid * 16 + k * 4096) : "memory");
        {
#pragma unroll
            for (int s = 0; s < 6; s++) {
                mbar_wait(bars + BAR_FULL + s * 8, 1);
                WG_FENCE();
                mma_stage_rt(s, acc1, af, desc0, adesc0);
                WG_COMMIT();
                if (s < 2) epi_gelu(acc0, s, sbase + SM_B1 + tq * 64 + 8 * 256, rstd0, rstd1, af[32 + (s & 1)]);
                if (s == 2 || s == 3) {
                    uint32_t tmp[4];
                    epi_gelu(acc0, s, sbase + SM_B1 + tq * 64 + 8 * 256, rstd0, rstd1, tmp);
                    const int lrow = warp * 16 + (lane & 7) + ((lane >> 3) & 1) * 8;
                    stsm_x4(tmp, sbase + 8 * 16384 + lrow * 128 + (((s * 2 + (lane >> 4)) ^ (lrow & 7)) << 4));
                }
                if (s == 3) {
                    asm volatile("fence.proxy.async.shared::cta;" ::: "memory");
                    asm volatile("bar.sync %0, 128;" ::"r"(3 + wgid) : "memory");
                }
                if (s > 0) {
                    WG_WAIT(1);
                    if (sig) asm volatile("mbarrier.arrive.shared::cluster.b64 _, [%0];" ::"r"(rbar + (s - 1) * 8) : "memory");
                }
                if (s == 5) warp_arrive(bars + BAR_PARKFREE, lane);
            }
        }
        uint4* part = g_part + (size_t)((m * 9 * 8 + warp) * 8 + f) * (4 * 32) + lane;
        uint32_t stored = bars + BAR_STORED;
#pragma unroll 1
        for (int c = 1; c < 9; c += 2) {
            if (warp == 0) DBG(7 + (c >> 1));
            run_chunk<2>(acc0, acc1, af, 0, bars, desc0, adesc0, stored, par, part, sig, rbar, lane, 0.f, 0.f);
            run_chunk<2>(acc1, acc0, af, 1, bars, desc0, adesc0, stored + 8, par, part + 8 * 8 * 4 * 32, sig, rbar, lane, 0.f, 0.f);
            part += 2 * 8 * 8 * 4 * 32;
            stored += 16;
        }
        const int t0 = m * 128 + f * 16 + g;
        asm volatile("griddepcontrol.wait;" ::: "memory");
        const float g0 = __ldcg(&g_gate[t0]), g1 = __ldcg(&g_gate[t0 + 8]);
        WG_WAIT(0);
        fence_acc(acc1);
#pragma unroll
        for (int i = 0; i < 4; i++) epi_part(acc1, i, part, par);
        warp_arrive(stored, lane);
        if (warp == 0) DBG(11);
        {
            const uint32_t gA = pack_bf16(g0, g0), gB = pack_bf16(g1, g1);
            const uint32_t half2 = 0x3f003f00u, one2 = 0x3f803f80u;
            const uint32_t oA = hsub2_bf(one2, gA), oB = hsub2_bf(one2, gB);
            uint32_t* o32 = reinterpret_cast<uint32_t*>(out + (size_t)t0 * D_MODEL + 2 * tq) + warp * 4;
            const uint32_t lm = sbase + 16384 + (lane & 7) * 32 + ((lane >> 3) & 1) * 16 + warp * 256;
            const uint32_t a0 = sbase + (warp >> 1) * 512 + lane * 16 + (warp & 1) * 8;
            const uint32_t b2a = sbase + SM_B2 + (warp >> 1) * 32 + tq * 8 + (warp & 1) * 4;
#pragma unroll 1
            for (int c0 = 0; c0 < 9; c0 += 3) {
                uint2 v[3][8], av[3];
                uint32_t bb[3];
#pragma unroll
                for (int k = 0; k < 3; k++) {
                    const int c = c0 + k;
                    const uint32_t bo = red_buf(c);
                    mbar_wait(bars + BAR_LOADED + c * 8, 0);
#pragma unroll
                    for (int q = 0; q < 8; q++) v[k][q] = ssm::lds64(a0 + bo + q * 2048);
                    asm volatile("ldmatrix.sync.aligned.m8n8.x2.trans.shared.b16 {%0,%1}, [%2];"
                                 : "=r"(av[k].x), "=r"(av[k].y) : "r"(lm + bo) : "memory");
                    bb[k] = ssm::lds32(b2a + c * 128);
                }
                uint32_t bad = 0;
#pragma unroll
                for (int k = 0; k < 3; k++)
#pragma unroll
                    for (int q = 0; q < 8; q++) bad |= v[k][q].x ^ par;
                int tries = 0;
                while (__any_sync(0xffffffffu, bad & 1)) {
                    const uint2* ps = reinterpret_cast<const uint2*>(
                        g_part + ((m * 9 + c0) * 8 + f) * (8 * 4 * 32) + (warp >> 1) * 32 + lane) + (warp & 1);
                    bad = 0;
#pragma unroll
                    for (int k = 0; k < 3; k++)
#pragma unroll
                        for (int q = 0; q < 8; q++) {
                            unsigned long long w;
                            asm volatile("ld.relaxed.gpu.global.b64 %0, [%1];" : "=l"(w)
                                         : "l"(ps + k * (8 * 8 * 4 * 32 * 2) + q * 256) : "memory");
                            v[k][q] = make_uint2((uint32_t)w, (uint32_t)(w >> 32));
                            bad |= v[k][q].x ^ par;
                        }
                    if (++tries > (1 << 20)) asm volatile("trap;");
                }
#pragma unroll
                for (int k = 0; k < 3; k++) {
                    float sx0 = 0.f, sx1 = 0.f, sy0 = 0.f, sy1 = 0.f;
#pragma unroll
                    for (int q = 0; q < 8; q++) {
                        sx0 += bf_lo(v[k][q].x); sx1 += bf_hi(v[k][q].x);
                        sy0 += bf_lo(v[k][q].y); sy1 += bf_hi(v[k][q].y);
                    }
                    o32[(c0 + k) * 32] = hadd2_bf(hmul2_bf(gA, av[k].x), hmul2_bf(oA, hfma2_bf(pack_bf16(sx0, sx1), half2, bb[k])));
                    o32[(c0 + k) * 32 + 4 * D_MODEL] =
                        hadd2_bf(hmul2_bf(gB, av[k].y), hmul2_bf(oB, hfma2_bf(pack_bf16(sy0, sy1), half2, bb[k])));
                }
                if (warp == 0) DBG(32 + c0 / 3);
            }
        }
        asm volatile("barrier.cluster.arrive.release.aligned;\nbarrier.cluster.wait.acquire.aligned;" ::: "memory");
        if (warp == 0) DBG(13);
    }
}

typedef CUresult (*EncodeFn)(CUtensorMap*, CUtensorMapDataType, cuuint32_t, void*, const cuuint64_t*,
                             const cuuint64_t*, const cuuint32_t*, const cuuint32_t*, CUtensorMapInterleave,
                             CUtensorMapSwizzle, CUtensorMapL2promotion, CUtensorMapFloatOOBfill);

static void make_map(EncodeFn enc, CUtensorMap* m, const void* ptr, uint64_t cols, uint64_t rows, uint32_t box_c,
                     uint32_t box_r, CUtensorMapSwizzle swz = CU_TENSOR_MAP_SWIZZLE_128B) {
    cuuint64_t dim[2] = {cols, rows};
    cuuint64_t str[1] = {cols * 2};
    cuuint32_t box[2] = {box_c, box_r};
    cuuint32_t es[2] = {1, 1};
    enc(m, CU_TENSOR_MAP_DATA_TYPE_BFLOAT16, 2, const_cast<void*>(ptr), dim, str, box, es,
        CU_TENSOR_MAP_INTERLEAVE_NONE, swz, CU_TENSOR_MAP_L2_PROMOTION_L2_128B,
        CU_TENSOR_MAP_FLOAT_OOB_FILL_NONE);
}

}

extern "C" void kernel_launch(void* const* d_in, const int* in_sizes, int n_in, void* d_out, int out_size) {
    const bf16* u = (const bf16*)d_in[0];
    const bf16* A_re = (const bf16*)d_in[1];
    const bf16* A_im = (const bf16*)d_in[2];
    const bf16* B_re = (const bf16*)d_in[3];
    const bf16* B_im = (const bf16*)d_in[4];
    const bf16* C_re = (const bf16*)d_in[5];
    const bf16* C_im = (const bf16*)d_in[6];
    const bf16* log_dt = (const bf16*)d_in[7];
    const bf16* Dskip = (const bf16*)d_in[8];
    const bf16* w1 = (const bf16*)d_in[10];
    const bf16* b1 = (const bf16*)d_in[11];
    const bf16* w2 = (const bf16*)d_in[12];
    const bf16* b2 = (const bf16*)d_in[13];
    const bf16* gw = (const bf16*)d_in[14];
    bf16* out = (bf16*)d_out;

    static EncodeFn enc = nullptr;
    if (!enc) {
        void* fn = nullptr;
        cudaDriverEntryPointQueryResult q;
        cudaGetDriverEntryPoint("cuTensorMapEncodeTiled", &fn, cudaEnableDefault, &q);
        enc = (EncodeFn)fn;
        cudaFuncSetAttribute(mlp_kernel, cudaFuncAttributeMaxDynamicSharedMemorySize, MLP_SMEM);
        cudaFuncSetAttribute(ssm::ssm_kernel, cudaFuncAttributeMaxDynamicSharedMemorySize, ssm::K1_SMEM);
    }
    static void* aT_ptr = nullptr;
    if (!aT_ptr) cudaGetSymbolAddress(&aT_ptr, g_aT);
    CUtensorMap tmx, tmw1, tmw2, tma;
    make_map(enc, &tma, aT_ptr, L_SEQ, D_MODEL, 16, 64, CU_TENSOR_MAP_SWIZZLE_NONE);
    make_map(enc, &tmx, u, D_MODEL, L_SEQ, 64, 128);
    make_map(enc, &tmw1, w1, F_DIM, D_MODEL, 64, 48);
    make_map(enc, &tmw2, w2, D_MODEL, F_DIM, 64, 48);

    cudaStream_t st = cudaStreamPerThread;
    ssm::Params sp{A_re, A_im, B_re, B_im, C_re, C_im, log_dt, Dskip};
    CUtensorMap tmc, tmo;
    make_map(enc, &tmc, u, D_MODEL, L_SEQ, 8, 256, CU_TENSOR_MAP_SWIZZLE_NONE);
    make_map(enc, &tmo, aT_ptr, 64, D_MODEL * 32, 64, 32);
    ssm::ssm_kernel<<<ssm::K1_CTAS + ssm::K1_STAT, 128 * ssm::K1_WGS, ssm::K1_SMEM, st>>>(tmc, tmo, u, gw, sp);
    cudaLaunchConfig_t cfg = {};
    cfg.gridDim = dim3(128);
    cfg.blockDim = dim3(384);
    cfg.dynamicSmemBytes = MLP_SMEM;
    cfg.stream = st;
    cudaLaunchAttribute at[1];
    at[0].id = cudaLaunchAttributeProgrammaticStreamSerialization;
    at[0].val.programmaticStreamSerializationAllowed = 1;
    cfg.attrs = at;
    cfg.numAttrs = 1;
    cudaLaunchKernelEx(&cfg, mlp_kernel, tmx, tmw1, tmw2, tma, b1, b2, out);
}
```

```cpp
#include <cuda_runtime.h>
#include <cuda_bf16.h>
#include <cuda.h>
#include <stdint.h>

namespace {

constexpr int L_SEQ = 2048;
constexpr int D_MODEL = 576;
constexpr int F_DIM = 4608;
constexpr int N_MODES = 128;

typedef __nv_bfloat16 bf16;

__device__ uint2 g_rowstat[L_SEQ];
__device__ float g_gate[L_SEQ];
__device__ bf16 g_aT[D_MODEL * L_SEQ];
__device__ uint4 g_part[16 * 9 * 8 * 8 * 4 * 32];
__device__ unsigned g_stat_epoch[16];
__device__ unsigned g_epoch;

#define DBG(slot)
#define DBG1(slot)

__device__ __forceinline__ uint32_t smem_u32(const void* p) { return (uint32_t)__cvta_generic_to_shared(p); }
__device__ __forceinline__ float bf16r(float x) { return __bfloat162float(__float2bfloat16_rn(x)); }
__device__ __forceinline__ uint32_t pack_bf16(float lo, float hi) {
    uint32_t r;
    asm("cvt.rn.bf16x2.f32 %0, %1, %2;" : "=r"(r) : "f"(hi), "f"(lo));
    return r;
}
__device__ __forceinline__ float bf_lo(uint32_t v) { return __uint_as_float(v << 16); }
__device__ __forceinline__ float bf_hi(uint32_t v) { return __uint_as_float(v & 0xffff0000u); }

__device__ __forceinline__ void mbar_init(uint32_t bar, int cnt) {
    asm volatile("mbarrier.init.shared::cta.b64 [%0], %1;" ::"r"(bar), "r"(cnt));
}
__device__ __forceinline__ void mbar_expect(uint32_t bar, int bytes) {
    asm volatile("mbarrier.arrive.expect_tx.shared::cta.b64 _, [%0], %1;" ::"r"(bar), "r"(bytes) : "memory");
}
__device__ __forceinline__ void mbar_wait(uint32_t bar, int parity) {
    asm volatile(
        "{\n.reg .pred p;\n.reg .u32 n;\nmov.u32 n, 0;\n"
        "WAIT_LOOP:\n"
        "mbarrier.try_wait.parity.shared::cta.b64 p, [%0], %1;\n"
        "@p bra WAIT_DONE;\n"
        "add.u32 n, n, 1;\n"
        "setp.lt.u32 p, n, 4194304;\n"
        "@p bra WAIT_LOOP;\n"
        "trap;\n"
        "WAIT_DONE:\n}\n" ::"r"(bar), "r"(parity) : "memory");
}
__device__ __forceinline__ void tma2d(uint32_t dst, const CUtensorMap* m, int c0, int c1, uint32_t bar) {
    asm volatile(
        "cp.async.bulk.tensor.2d.shared::cluster.global.mbarrier::complete_tx::bytes [%0], [%1, {%3,%4}], [%2];"
        ::"r"(dst), "l"(m), "r"(bar), "r"(c0), "r"(c1) : "memory");
}
__device__ __forceinline__ void tma2d_mc(uint32_t dst, const CUtensorMap* m, int c0, int c1, uint32_t bar,
                                         uint16_t mask) {
    asm volatile(
        "cp.async.bulk.tensor.2d.shared::cluster.global.mbarrier::complete_tx::bytes.multicast::cluster.L2::cache_hint "
        "[%0], [%1, {%3,%4}], [%2], %5, %6;"
        ::"r"(dst), "l"(m), "r"(bar), "r"(c0), "r"(c1), "h"(mask), "l"(0x12F0000000000000ull) : "memory");
}
__device__ __forceinline__ void ldsm_x4(uint32_t (&r)[4], uint32_t addr) {
    asm volatile("ldmatrix.sync.aligned.m8n8.x4.shared.b16 {%0,%1,%2,%3}, [%4];"
                 : "=r"(r[0]), "=r"(r[1]), "=r"(r[2]), "=r"(r[3]) : "r"(addr) : "memory");
}
#define WG_FENCE() asm volatile("wgmma.fence.sync.aligned;\n" ::: "memory")
#define WG_COMMIT() asm volatile("wgmma.commit_group.sync.aligned;\n" ::: "memory")
#define WG_WAIT(n) asm volatile("wgmma.wait_group.sync.aligned %0;\n" ::"n"(n) : "memory")

template <int SCALE_D, int OFF>
__device__ __forceinline__ void wgmma_rs_n64(float (&d)[32], const uint32_t (&a)[4], uint32_t desc_lo) {
    asm volatile(
        "{\n.reg .pred p;\n.reg .b32 lo;\n.reg .b64 dsc;\nsetp.ne.b32 p, %37, 0;\n"
        "add.u32 lo, %36, %38;\nmov.b64 dsc, {lo, 0x40000040};\n"
        "wgmma.mma_async.sync.aligned.m64n64k16.f32.bf16.bf16 "
        "{%0,%1,%2,%3,%4,%5,%6,%7,%8,%9,%10,%11,%12,%13,%14,%15,%16,%17,%18,%19,%20,%21,%22,%23,%24,%25,%26,%27,%28,%29,%30,%31},"
        "{%32,%33,%34,%35}, dsc, p, 1, 1, 1;\n}\n"
        : "+f"(d[0]), "+f"(d[1]), "+f"(d[2]), "+f"(d[3]), "+f"(d[4]), "+f"(d[5]), "+f"(d[6]), "+f"(d[7]),
          "+f"(d[8]), "+f"(d[9]), "+f"(d[10]), "+f"(d[11]), "+f"(d[12]), "+f"(d[13]), "+f"(d[14]), "+f"(d[15]),
          "+f"(d[16]), "+f"(d[17]), "+f"(d[18]), "+f"(d[19]), "+f"(d[20]), "+f"(d[21]), "+f"(d[22]), "+f"(d[23]),
          "+f"(d[24]), "+f"(d[25]), "+f"(d[26]), "+f"(d[27]), "+f"(d[28]), "+f"(d[29]), "+f"(d[30]), "+f"(d[31])
        : "r"(a[0]), "r"(a[1]), "r"(a[2]), "r"(a[3]), "r"(desc_lo), "n"(SCALE_D), "n"(OFF));
}
template <int OFF, int AOFF>
__device__ __forceinline__ void wgmma_ss_n64(float (&d)[32], uint32_t adesc_lo, uint32_t desc_lo) {
    asm volatile(
        "{\n.reg .pred p;\n.reg .b32 lo;\n.reg .b64 dsc, dsa;\nsetp.ne.b32 p, 1, 0;\n"
        "add.u32 lo, %33, %34;\nmov.b64 dsc, {lo, 0x40000040};\n"
        "add.u32 lo, %32, %35;\nmov.b64 dsa, {lo, 0x40000040};\n"
        "wgmma.mma_async.sync.aligned.m64n64k16.f32.bf16.bf16 "
        "{%0,%1,%2,%3,%4,%5,%6,%7,%8,%9,%10,%11,%12,%13,%14,%15,%16,%17,%18,%19,%20,%21,%22,%23,%24,%25,%26,%27,%28,%29,%30,%31},"
        "dsa, dsc, p, 1, 1, 0, 1;\n}\n"
        : "+f"(d[0]), "+f"(d[1]), "+f"(d[2]), "+f"(d[3]), "+f"(d[4]), "+f"(d[5]), "+f"(d[6]), "+f"(d[7]),
          "+f"(d[8]), "+f"(d[9]), "+f"(d[10]), "+f"(d[11]), "+f"(d[12]), "+f"(d[13]), "+f"(d[14]), "+f"(d[15]),
          "+f"(d[16]), "+f"(d[17]), "+f"(d[18]), "+f"(d[19]), "+f"(d[20]), "+f"(d[21]), "+f"(d[22]), "+f"(d[23]),
          "+f"(d[24]), "+f"(d[25]), "+f"(d[26]), "+f"(d[27]), "+f"(d[28]), "+f"(d[29]), "+f"(d[30]), "+f"(d[31])
        : "r"(adesc_lo), "r"(desc_lo), "n"(OFF), "n"(AOFF));
}
constexpr int NAF = 34;
template <int S, int FIRST>
__device__ __forceinline__ void mma_stage(float (&d)[32], const uint32_t (&af)[NAF][4], uint32_t desc_lo,
                                          uint32_t adesc_lo) {
    constexpr int B = (S * 96 * 128) >> 4;
    wgmma_rs_n64<FIRST ? 0 : 1, B + 0 * 128>(d, af[S * 6 + 0], desc_lo);
    wgmma_rs_n64<1, B + 1 * 128>(d, af[S * 6 + 1], desc_lo);
    wgmma_rs_n64<1, B + 2 * 128>(d, af[S * 6 + 2], desc_lo);
    wgmma_rs_n64<1, B + 3 * 128>(d, af[S * 6 + 3], desc_lo);
    if constexpr (S < 5) {
        wgmma_rs_n64<1, B + 4 * 128>(d, af[S * 6 + 4], desc_lo);
        wgmma_rs_n64<1, B + 5 * 128>(d, af[S * 6 + 5], desc_lo);
    } else {
        wgmma_ss_n64<B + 4 * 128, 4>(d, adesc_lo, desc_lo);
        wgmma_ss_n64<B + 5 * 128, 6>(d, adesc_lo, desc_lo);
    }
}
__device__ __forceinline__ void mma_stage_rt(int s, float (&d)[32], const uint32_t (&af)[NAF][4], uint32_t desc_lo,
                                             uint32_t adesc_lo) {
    if (s == 0) mma_stage<0, 1>(d, af, desc_lo, adesc_lo);
    if (s == 1) mma_stage<1, 0>(d, af, desc_lo, adesc_lo);
    if (s == 2) mma_stage<2, 0>(d, af, desc_lo, adesc_lo);
    if (s == 3) mma_stage<3, 0>(d, af, desc_lo, adesc_lo);
    if (s == 4) mma_stage<4, 0>(d, af, desc_lo, adesc_lo);
    if (s == 5) mma_stage<5, 0>(d, af, desc_lo, adesc_lo);
}
__device__ __forceinline__ void stsm_x4(const uint32_t (&r)[4], uint32_t addr) {
    asm volatile("stmatrix.sync.aligned.m8n8.x4.shared.b16 [%4], {%0,%1,%2,%3};"
                 ::"r"(r[0]), "r"(r[1]), "r"(r[2]), "r"(r[3]), "r"(addr) : "memory");
}
__device__ __forceinline__ void fence_acc(float (&d)[32]) {
#pragma unroll
    for (int i = 0; i < 32; i++) asm volatile("" : "+f"(d[i])::"memory");
}

__device__ __forceinline__ uint32_t hadd2_bf(uint32_t a, uint32_t b) {
    uint32_t r;
    asm("add.rn.bf16x2 %0, %1, %2;" : "=r"(r) : "r"(a), "r"(b));
    return r;
}
__device__ __forceinline__ uint32_t hsub2_bf(uint32_t a, uint32_t b) {
    uint32_t r;
    asm("sub.rn.bf16x2 %0, %1, %2;" : "=r"(r) : "r"(a), "r"(b));
    return r;
}
__device__ __forceinline__ uint32_t hmul2_bf(uint32_t a, uint32_t b) {
    uint32_t r;
    asm("mul.rn.bf16x2 %0, %1, %2;" : "=r"(r) : "r"(a), "r"(b));
    return r;
}
__device__ __forceinline__ uint32_t hfma2_bf(uint32_t a, uint32_t b, uint32_t c) {
    uint32_t r;
    asm("fma.rn.bf16x2 %0, %1, %2, %3;" : "=r"(r) : "r"(a), "r"(b), "r"(c));
    return r;
}
namespace ssm {
constexpr int O_H = 0;
constexpr int O_L = 12288;
constexpr int HL_END = O_L + 16384;
constexpr int O_Q = 0;
constexpr int O_Q12 = 5120;
constexpr int O_Q34 = O_Q12 + 1280;
constexpr int O_Y12 = O_Q34 + 2048 - 2176;
constexpr int O_Y34 = O_Y12 + 8704 - 4352;
constexpr int O_W3 = O_Y34 + 8704 + 256;
constexpr int O_W4 = O_W3 + 2048 + 256;
constexpr int O_W5 = O_W4 + 2048;
constexpr int O_U = HL_END;
constexpr int O_RAW = O_U + 6144;
constexpr int O_W1 = O_U + 6144 + 256;
constexpr int O_W2 = O_W1 + 3072 + 256;
constexpr int O_ST = O_RAW;
constexpr int O_KN = O_W2 + 3072;
constexpr int O_A12 = O_KN + 1344;
constexpr int O_A3 = O_A12 + 384;
constexpr int O_KQ = O_A3 + 304;
constexpr int WG_BYTES = 44032;
static_assert(O_W5 + 2048 <= HL_END && O_KQ + 16 <= WG_BYTES && WG_BYTES % 1024 == 0 && O_RAW + 8192 <= WG_BYTES, "map");

struct cplx { float r, i; };
__device__ __forceinline__ cplx cmul(cplx a, cplx b) {
    cplx o;
    o.r = fmaf(a.r, b.r, -a.i * b.i);
    o.i = fmaf(a.r, b.i, a.i * b.r);
    return o;
}
__device__ __forceinline__ cplx cexp_l(float lr, float li, float l) {
    const float e = exp2f((lr * l) * 1.4426950408889634f);
    const float ang = li * l;
    const float k = rintf(ang * 0.15915494309189535f);
    float r = fmaf(k, -6.2831854820251465f, ang);
    r = fmaf(k, 1.7484556000744487e-07f, r);
    cplx o;
    o.r = e * __cosf(r);
    o.i = e * __sinf(r);
    return o;
}
template <typename T> __device__ __forceinline__ T* sp(uint32_t a) {
    return reinterpret_cast<T*>(__cvta_shared_to_generic(a));
}
__device__ __forceinline__ void sts32(uint32_t a, uint32_t v) { *sp<uint32_t>(a) = v; }
__device__ __forceinline__ void sts16(uint32_t a, uint32_t v) { *sp<unsigned short>(a) = (unsigned short)v; }
__device__ __forceinline__ uint32_t lds16(uint32_t a) { return *sp<unsigned short>(a); }
__device__ __forceinline__ uint32_t lds32(uint32_t a) { return *sp<uint32_t>(a); }
__device__ __forceinline__ float ldsf(uint32_t a) { return *sp<float>(a); }
__device__ __forceinline__ uint2 lds64(uint32_t a) { return *sp<uint2>(a); }
__device__ __forceinline__ void sts64(uint32_t a, uint32_t x, uint32_t y) { *sp<uint2>(a) = make_uint2(x, y); }
__device__ __forceinline__ void sts64f(uint32_t a, float x, float y) { *sp<float2>(a) = make_float2(x, y); }
__device__ __forceinline__ void sts128(uint32_t a, uint32_t x, uint32_t y, uint32_t z, uint32_t w) {
    *sp<uint4>(a) = make_uint4(x, y, z, w);
}
__device__ __forceinline__ uint4 lds128(uint32_t a) { return *sp<uint4>(a); }
__device__ __forceinline__ void wg_bar(int id) { asm volatile("bar.sync %0, 128;" ::"r"(id) : "memory"); }
__device__ __forceinline__ uint32_t u_addr(uint32_t sb, int grp) {
    const int gq = grp + 128;
    return sb + O_U + (gq >> 3) * 128 + (((gq ^ (gq >> 3)) & 7) << 4);
}
template <int SCALE_D, int OA, int OB>
__device__ __forceinline__ void wgmma_ss_n32(float (&d)[16], uint32_t dl) {
    asm volatile(
        "{\n.reg .pred p;\n.reg .b32 lo;\n.reg .b64 x, y;\nsetp.ne.b32 p, %17, 0;\n"
        "add.u32 lo, %16, %18;\nmov.b64 x, {lo, 0x40000040};\nadd.u32 lo, %16, %19;\nmov.b64 y, {lo, 0x40000040};\n"
        "wgmma.mma_async.sync.aligned.m64n32k16.f32.bf16.bf16 "
        "{%0,%1,%2,%3,%4,%5,%6,%7,%8,%9,%10,%11,%12,%13,%14,%15}, x, y, p, 1, 1, 0, 0;\n}\n"
        : "+f"(d[0]), "+f"(d[1]), "+f"(d[2]), "+f"(d[3]), "+f"(d[4]), "+f"(d[5]), "+f"(d[6]), "+f"(d[7]),
          "+f"(d[8]), "+f"(d[9]), "+f"(d[10]), "+f"(d[11]), "+f"(d[12]), "+f"(d[13]), "+f"(d[14]), "+f"(d[15])
        : "r"(dl), "n"(SCALE_D), "n"(OA), "n"(OB));
}
template <int OB>
__device__ __forceinline__ void wgmma_rs_n32(float (&d)[16], uint32_t a0, uint32_t a1, uint32_t a2, uint32_t a3,
                                             uint32_t dl) {
    asm volatile(
        "{\n.reg .pred p;\n.reg .b32 lo;\n.reg .b64 y;\nsetp.ne.b32 p, 1, 0;\n"
        "add.u32 lo, %20, %21;\nmov.b64 y, {lo, 0x40000040};\n"
        "wgmma.mma_async.sync.aligned.m64n32k16.f32.bf16.bf16 "
        "{%0,%1,%2,%3,%4,%5,%6,%7,%8,%9,%10,%11,%12,%13,%14,%15}, {%16,%17,%18,%19}, y, p, 1, 1, 0;\n}\n"
        : "+f"(d[0]), "+f"(d[1]), "+f"(d[2]), "+f"(d[3]), "+f"(d[4]), "+f"(d[5]), "+f"(d[6]), "+f"(d[7]),
          "+f"(d[8]), "+f"(d[9]), "+f"(d[10]), "+f"(d[11]), "+f"(d[12]), "+f"(d[13]), "+f"(d[14]), "+f"(d[15])
        : "r"(a0), "r"(a1), "r"(a2), "r"(a3), "r"(dl), "n"(OB));
}
template <int KS> struct KgenSteps {
    static __device__ __forceinline__ void run(float (&d)[16], uint32_t dl) {
        KgenSteps<KS - 1>::run(d, dl);
        constexpr int k = KS - 1;
        wgmma_ss_n32<(k > 0), (O_H + (k / 4) * 3072 + (k % 4) * 32) / 16, (O_L + (k / 4) * 4096 + (k % 4) * 32) / 16>(d, dl);
    }
};
template <> struct KgenSteps<0> { static __device__ __forceinline__ void run(float (&)[16], uint32_t) {} };
template <int K0, int N, int I> struct NearSteps {
    static __device__ __forceinline__ void run(float (&d)[16], const uint4 (&f)[N], uint32_t dl) {
        NearSteps<K0, N, I - 1>::run(d, f, dl);
        constexpr int k = K0 + I - 1, dd = k / 4, kk = 4 * dd - (k - 3);
        wgmma_rs_n32<(O_U + (16 - dd) * 128 + kk * 32) / 16>(d, f[I - 1].x, f[I - 1].y, f[I - 1].z, f[I - 1].w, dl);
    }
};
template <int K0, int N> struct NearSteps<K0, N, 0> {
    static __device__ __forceinline__ void run(float (&)[16], const uint4 (&)[N], uint32_t) {}
};
template <int N>
__device__ __forceinline__ void load_toep(uint4 (&f)[N], uint32_t addr, uint32_t& prev) {
#pragma unroll
    for (int k = 0; k < N; k++)
    { const uint2 v = lds64(addr + k * 128); f[k].x = v.x; f[k].y = v.y; }
#pragma unroll
    for (int k = 0; k < N; k++) {
        f[k].z = prev;
        f[k].w = f[k].x;
        prev = f[k].y;
    }
}
__device__ __forceinline__ void mma16816(float (&d)[4], uint32_t a0, uint32_t a1, uint32_t a2, uint32_t b0,
                                         uint32_t b1) {
    asm("mma.sync.aligned.m16n8k16.row.col.f32.bf16.bf16.f32 {%0,%1,%2,%3}, {%4,%5,%6,%4}, {%7,%8}, {%0,%1,%2,%3};"
                 : "+f"(d[0]), "+f"(d[1]), "+f"(d[2]), "+f"(d[3])
                 : "r"(a0), "r"(a1), "r"(a2), "r"(b0), "r"(b1));
}
__device__ __forceinline__ uint4 ldsm_x4_t(uint32_t addr) {
    uint4 r;
    asm volatile("ldmatrix.sync.aligned.m8n8.x4.trans.shared.b16 {%0,%1,%2,%3}, [%4];"
                 : "=r"(r.x), "=r"(r.y), "=r"(r.z), "=r"(r.w) : "r"(addr));
    return r;
}
struct Params { const bf16 *A_re, *A_im, *B_re, *B_im, *C_re, *C_im, *log_dt, *Dskip; };
struct ModeIn { float ar, ai, br, bi, cr, ci, ldt, dsk; };
__device__ __forceinline__ ModeIn load_mode(const Params& p, int d, int n) {
    ModeIn m;
    const int i = d * N_MODES + n;
    m.ar = __bfloat162float(p.A_re[i]); m.ai = __bfloat162float(p.A_im[i]);
    m.br = __bfloat162float(p.B_re[i]); m.bi = __bfloat162float(p.B_im[i]);
    m.cr = __bfloat162float(p.C_re[i]); m.ci = __bfloat162float(p.C_im[i]);
    m.ldt = __bfloat162float(p.log_dt[d]); m.dsk = __bfloat162float(p.Dskip[d]);
    return m;
}

__device__ __forceinline__ void gen_powers(const ModeIn& mi, uint32_t sb, int t) {
    const float dt = bf16r(expf(mi.ldt));
    const float lr = dt * mi.ar, li = dt * mi.ai;
    const float br = dt * mi.br, bi = dt * mi.bi;
    cplx c;
    c.r = mi.cr * br - mi.ci * bi;
    c.i = mi.cr * bi + mi.ci * br;
    const cplx z = cexp_l(lr, li, 1.f), wv = cexp_l(lr, li, 8.f), Z = cexp_l(lr, li, 256.f);
    const cplx z2 = cmul(z, z), z4 = cmul(z2, z2);
    const uint32_t x0 = ((t & 31) >> 2) * 16 + (t & 3) * 4;
    uint32_t xs[8];
#pragma unroll
    for (int j = 0; j < 8; j++) xs[j] = sb + (x0 ^ (j << 4));
    const uint32_t ho = O_H + (t >> 5) * 3072, lo_ = O_L + (t >> 5) * 4096;
#define PUT_H(row, v) sts32(xs[(row) & 7] + ho + (row) * 128, pack_bf16((v).r, -(v).i))
#define PUT_L(row, v) sts32(xs[(row) & 7] + lo_ + (row) * 128, pack_bf16((v).r, (v).i))
    cplx h = c;
    PUT_H(0, h);
#pragma unroll
    for (int k = 1; k < 8; k++) { h = cmul(h, z); PUT_H(k, h); }
    cplx hz = cmul(c, Z);
    PUT_H(8, hz);
    { cplx a = cmul(hz, z2); PUT_H(9, a); a = cmul(hz, z4); PUT_H(10, a); a = cmul(a, z2); PUT_H(11, a); }
    hz = cmul(hz, Z); PUT_H(12, hz);
    { cplx a = cmul(hz, z4); PUT_H(13, a); }
    hz = cmul(hz, Z); PUT_H(14, hz);
    { cplx a = cmul(hz, z4); PUT_H(15, a); }
#pragma unroll
    for (int k = 16; k < 21; k++) { hz = cmul(hz, Z); PUT_H(k, hz); }
    const cplx w2 = cmul(wv, wv);
    cplx le, lo = wv;
    le.r = 1.f; le.i = 0.f;
    uint32_t lb = lo_;
#pragma unroll 1
    for (int kb = 0; kb < 4; kb++) {
#pragma unroll
        for (int k = 0; k < 8; k += 2) {
            sts32(xs[k] + lb + k * 128, pack_bf16(le.r, le.i));
            sts32(xs[k + 1] + lb + (k + 1) * 128, pack_bf16(lo.r, lo.i));
            le = cmul(le, w2); lo = cmul(lo, w2);
        }
        lb += 1024;
    }
}

__device__ __forceinline__ uint4 pack8(const float (&v)[8]) {
    return make_uint4(pack_bf16(v[0], v[1]), pack_bf16(v[2], v[3]), pack_bf16(v[4], v[5]), pack_bf16(v[6], v[7]));
}
__device__ __forceinline__ void st16B(uint32_t a, const uint4& v) { *sp<uint4>(a) = v; }

__device__ __forceinline__ void build_windows(uint32_t sb, int t) {
    if (t < 64) {
        const int which = t >> 4;
        sts128(sb + (which == 0 ? O_W1 : which == 1 ? O_W2 : which == 2 ? O_W3 : O_W4) - 256 + (t & 15) * 16, 0, 0, 0, 0);
    }
#pragma unroll
    for (int r = 0; r < 2; r++) {
        const int grp = t + r * 128;
        if (grp < 192) {
            const uint4 c0 = lds128(u_addr(sb, grp - 2)), c1 = lds128(u_addr(sb, grp - 1)), c2 = lds128(u_addr(sb, grp));
            float v[24];
            const uint32_t ww[12] = {c0.x, c0.y, c0.z, c0.w, c1.x, c1.y, c1.z, c1.w, c2.x, c2.y, c2.z, c2.w};
#pragma unroll
            for (int i = 2; i < 11; i++) { v[2 * i] = bf_lo(ww[i]); v[2 * i + 1] = bf_hi(ww[i]); }
            float p2[15];
#pragma unroll
            for (int j = 0; j < 15; j++) p2[j] = v[5 + j] + v[6 + j];
            float b1[8], b2[8];
#pragma unroll
            for (int i = 0; i < 8; i++) {
                b2[i] = p2[i + 6] + v[13 + i];
                b1[i] = p2[i + 1] + p2[i + 3] + v[10 + i];
            }
            st16B(sb + O_W1 + grp * 16, pack8(b1));
            st16B(sb + O_W2 + grp * 16, pack8(b2));
            if (r == 0) {
                float b3[8], b5[8];
#pragma unroll
                for (int i = 0; i < 8; i++) {
                    b3[i] = b1[i] + v[11 + i] + v[5 + i];
                    b5[i] = p2[i + 7];
                }
                st16B(sb + O_W3 + grp * 16, pack8(b3));
                st16B(sb + O_W5 + grp * 16, pack8(b5));
                st16B(sb + O_W4 + grp * 16, make_uint4(hadd2_bf(ww[6], ww[2]), hadd2_bf(ww[7], ww[3]),
                                                       hadd2_bf(ww[8], ww[4]), hadd2_bf(ww[9], ww[5])));
            }
        }
    }
}

__device__ __forceinline__ void build_tables(float (&kd)[16], float dskip, uint32_t sb, int t, int bar) {
    const int lane = t & 31, w = t >> 5, g = lane >> 2, tq = lane & 3;
    if (w == 0) {
        if (lane == 0) kd[0] += dskip;
        const uint32_t kn = sb + O_KN + 128;
#pragma unroll
        for (int j = 0; j < 4; j++) {
            const int lo = 8 * j + 2 * tq;
            const uint32_t p0 = pack_bf16(kd[4 * j], kd[4 * j + 1]), p1 = pack_bf16(kd[4 * j + 2], kd[4 * j + 3]);
            sts16(kn + (g + 8 * lo) * 2, p0);
            sts16(kn + (g + 8 * lo + 8) * 2, p0 >> 16);
            if (g < 4) {
#pragma unroll
                for (int e = 0; e < 2; e++) {
                    const uint32_t val = e ? (p1 >> 16) : p1, ad = kn + (256 + 2 * g + 8 * (lo + e)) * 2;
                    sts16(ad, val);
                    if (!(g & 1)) {
                        sts16(ad + 2, val);
                        if (g + lo + e > 0) sts16(ad - 2, val);
                    }
                }
            } else {
#pragma unroll
                for (int e = 0; e < 2; e++) {
                    const uint32_t val = e ? (p1 >> 16) : p1;
                    const int i8 = 64 + (g >= 6 ? 32 : 0) + lo + e;
                    if (j > 0 || i8 >= 66) {
                        sts16(sb + O_A12 + (i8 - 48) * 4 - ((g & 1) ? 0 : 2), val);
                    } else if (g & 1) {
                        sts16(kn + (8 * i8 + 3) * 2, val); sts16(kn + (8 * i8 + 4) * 2, val); sts16(kn + (8 * i8 + 5) * 2, val);
                    } else {
#pragma unroll
                        for (int dd = -2; dd <= 2; dd++)
                            if (i8 == 65 || dd >= -1) sts16(kn + (8 * i8 + dd) * 2, val);
                    }
                }
            }
        }
    } else if (w == 1) {
        if (g < 4) {
#pragma unroll
            for (int j = 0; j < 4; j++) {
                const int i8 = 128 + 32 * g + 8 * j + 2 * tq;
                const uint32_t p0 = pack_bf16(kd[4 * j], kd[4 * j + 1]);
                if (i8 == 128) { sts16(sb + O_A12 + (127 - 48) * 4 + 2, p0); sts16(sb + O_KQ, p0); }
                else sts16(sb + O_A3 + (i8 - 1 - 112) * 2, p0);
                sts16(sb + O_A3 + (i8 - 112) * 2, p0 >> 16);
            }
        } else if (lane == 16) {
            sts16(sb + O_A3 + (255 - 112) * 2, pack_bf16(kd[0], 0.f));
        }
    }
    wg_bar(bar);
    DBG1(4);
    {
#pragma unroll
        for (int r = 0; r < 2; r++) {
            const int i = t + r * 128;
            if (i < 160) {
                const uint32_t ka = sb + O_KN + (4 * i + 8) * 2;
                const uint32_t wm = lds32(ka - 4), w3 = lds32(ka + 12);
                const uint2 wa = lds64(ka), wb = lds64(ka + 16);
                const uint32_t w0 = wa.x, w1 = wa.y, w4 = wb.x, w5 = wb.y;
                sts128(sb + O_Q + i * 32, __byte_perm(w0, wm, 0x7610), __byte_perm(w4, w3, 0x7610),
                       __byte_perm(w0, w0, 0x1032), __byte_perm(w4, w4, 0x1032));
                sts128(sb + O_Q + i * 32 + 16, __byte_perm(w1, w0, 0x7610), __byte_perm(w5, w4, 0x7610),
                       __byte_perm(w1, w1, 0x1032), __byte_perm(w5, w5, 0x1032));
            }
        }
        {
            const uint32_t aa = sb + O_A3 + (8 + t) * 2;
            const uint32_t p0 = lds16(aa) | (lds16(aa - 2) << 16), p1 = lds16(aa + 16) | (lds16(aa + 14) << 16);
            const uint32_t msk = (t & 1) ? 0x0000ffffu : 0xffff0000u;
            sts128(sb + O_Q34 + t * 16, p0, p1, p0 & msk, p1 & msk);
        }
        if (t >= 48) {
            const uint32_t aa = sb + O_A12 + (t - 48 + 8) * 4;
            const uint32_t e0 = lds32(aa), e1 = lds32(aa - 4), f0 = lds32(aa + 32), f1 = lds32(aa + 28);
            sts128(sb + O_Q12 + (t - 48) * 16, __byte_perm(e0, e1, 0x7632), __byte_perm(f0, f1, 0x7632),
                   __byte_perm(e0, e1, 0x5410), __byte_perm(f0, f1, 0x5410));
        }
    }
}

__device__ __forceinline__ void convolve(int d, uint32_t sb, int t, int bar, const CUtensorMap* tmo) {
    const int lane = t & 31, w = t >> 5, g = lane >> 2, tq = lane & 3;
    const uint32_t dl = (sb & 0x3FFFF) >> 4;
    float y[16];
#pragma unroll
    for (int i = 0; i < 16; i++) y[i] = 0.f;
    {
        const uint32_t qa = sb + O_Q + (16 * w + g - 2 * tq + 56 - 48) * 8;
        uint32_t prev = 0;
        uint32_t qp = qa, du = dl;
#pragma unroll 1
        for (int jj = 0; jj < 4; jj++) {
            uint4 F[8];
            load_toep<8>(F, qp, prev);
            WG_FENCE();
            NearSteps<0, 8, 8>::run(y, F, du);
            WG_COMMIT();
            WG_WAIT(0);
            qp += 8 * 128;
            du -= 16;
        }
        uint4 FC[5];
        load_toep<5>(FC, qp, prev);
        WG_FENCE();
        NearSteps<0, 5, 5>::run(y, FC, du);
        WG_COMMIT();
        WG_WAIT(0);
#pragma unroll
        for (int i = 0; i < 16; i++) asm volatile("" : "+f"(y[i])::"memory");
    }
    DBG1(6);
    {
        const int par = w & 1;
        const uint32_t qoff = sb + (g - 2 * tq) * 16;
        const uint32_t roff = sb + (lane & 15) * 16 + par * 256;
        const uint32_t yoff = sb + (136 * par + 8 * g + 2 * tq) * 4;
        if (w < 2) {
            const uint32_t wb = roff + ((lane >> 4) ? O_W2 : O_W1);
            uint4 f[5];
#pragma unroll
            for (int q = 4; q <= 8; q++) f[q - 4] = lds128(qoff + O_Q12 + (16 * q - 56) * 16);
            uint4 bt[12];
#pragma unroll
            for (int i = 0; i < 6; i++) {
                if (i == 0) bt[0] = ldsm_x4_t(wb - 256);
                bt[2 * i + 1] = ldsm_x4_t(wb + (2 * i) * 256);
                if (i > 0) bt[2 * i] = ldsm_x4_t(wb + (2 * i - 1) * 256);
                float a0[4] = {0.f, 0.f, 0.f, 0.f}, a1[4] = {0.f, 0.f, 0.f, 0.f};
#pragma unroll
                for (int q = 4; q <= 8; q++) {
                    const int k = 2 * i + 4 - q;
                    if (k >= -1) {
                        mma16816(a0, f[q - 4].x, f[q - 4].y, q > 4 ? f[q > 4 ? q - 5 : 0].y : 0u, bt[k + 1].x, bt[k + 1].y);
                        mma16816(a1, f[q - 4].z, f[q - 4].w, q > 4 ? f[q > 4 ? q - 5 : 0].w : 0u, bt[k + 1].z, bt[k + 1].w);
                    }
                }
                const uint32_t ya = yoff + O_Y12 + 136 * (4 + 2 * i) * 4;
                sts64f(ya, a0[0] + a1[0], a0[1] + a1[1]);
                sts64f(ya + 256, a0[2] + a1[2], a0[3] + a1[3]);
            }
        } else {
            const uint32_t wb = roff + ((lane >> 4) ? O_W4 : O_W3);
            uint4 bt[8];
#pragma unroll
            for (int k = 0; k < 8; k++) bt[k] = ldsm_x4_t(wb + (k - 1) * 256);
            const uint4 b5a = ldsm_x4_t(roff + O_W5 + (lane >> 4) * 512), b5b = ldsm_x4_t(roff + O_W5 + 1024 + (lane >> 4) * 512);
            const uint32_t kq = lds16(sb + O_KQ);
            const uint32_t dg = (g == 2 * tq) ? kq : ((g == 2 * tq + 1) ? (kq << 16) : 0u);
            float acc[4][4];
#pragma unroll
            for (int i = 0; i < 4; i++)
#pragma unroll
                for (int j = 0; j < 4; j++) acc[i][j] = 0.f;
            mma16816(acc[0], dg, 0u, 0u, b5a.x, b5a.y);
            mma16816(acc[1], dg, 0u, 0u, b5a.z, b5a.w);
            mma16816(acc[2], dg, 0u, 0u, b5b.x, b5b.y);
            mma16816(acc[3], dg, 0u, 0u, b5b.z, b5b.w);
            uint32_t pa = 0, pb = 0;
#pragma unroll
            for (int q = 8; q <= 15; q++) {
                const uint4 f = lds128(qoff + O_Q34 + (16 * q - 120) * 16);
#pragma unroll
                for (int i = 0; i < 4; i++) {
                    const int k = 2 * i + 8 - q;
                    if (k >= -1) mma16816(acc[i], f.x, f.y, pa, bt[k + 1].x, bt[k + 1].y);
                }
#pragma unroll
                for (int i = 0; i < 4; i++) {
                    const int k = 2 * i + 8 - q;
                    if (k >= -1) mma16816(acc[i], f.z, f.w, pb, bt[k + 1].z, bt[k + 1].w);
                }
                pa = f.y; pb = f.w;
            }
#pragma unroll
            for (int i = 0; i < 4; i++) {
                const uint32_t ya = yoff + O_Y34 + 136 * (8 + 2 * i) * 4;
                sts64f(ya, acc[i][0], acc[i][1]);
                sts64f(ya + 256, acc[i][2], acc[i][3]);
            }
        }
    }
    wg_bar(bar);
    DBG1(7);
    {
        const uint32_t yb = sb + (136 * tq + 16 * w + g) * 4;
#pragma unroll
        for (int j = 1; j < 4; j++)
#pragma unroll
            for (int e = 0; e < 4; e++) {
                const uint32_t o = yb + (544 * j + 64 * (e & 1) + 8 * (e >> 1)) * 4;
                y[4 * j + e] += ldsf(o + O_Y12);
                if (j >= 2) y[4 * j + e] += ldsf(o + O_Y34);
            }
#pragma unroll
        for (int jp = 0; jp < 2; jp++) {
            const int a = 8 * (2 * jp + (lane >> 4)) + (lane & 7);
            const uint32_t addr = sb + O_ST + a * 128 + (((2 * w + ((lane >> 3) & 1)) ^ (lane & 7)) << 4);
            asm volatile("stmatrix.sync.aligned.m8n8.x4.trans.shared.b16 [%0], {%1,%2,%3,%4};" ::"r"(addr),
                         "r"(pack_bf16(y[8 * jp + 0], y[8 * jp + 1])), "r"(pack_bf16(y[8 * jp + 2], y[8 * jp + 3])),
                         "r"(pack_bf16(y[8 * jp + 4], y[8 * jp + 5])), "r"(pack_bf16(y[8 * jp + 6], y[8 * jp + 7]))
                         : "memory");
        }
        asm volatile("fence.proxy.async.shared::cta;" ::: "memory");
        wg_bar(bar);
        if (t == 0) {
            asm volatile("cp.async.bulk.tensor.2d.global.shared::cta.bulk_group [%0, {%1, %2}], [%3];"
                         ::"l"(tmo), "r"(0), "r"(d * 32), "r"(sb + O_ST) : "memory");
            asm volatile("cp.async.bulk.commit_group;" ::: "memory");
            asm volatile("cp.async.bulk.wait_group.read 0;" ::: "memory");
        }
        DBG1(8);
    }
}

constexpr int K1_WGS = 5;
constexpr int O_XTRA = K1_WGS * WG_BYTES;
constexpr int K1_SMEM = O_XTRA + 3 * 4096;
constexpr int K1_CTAS = (D_MODEL + K1_WGS - 1) / K1_WGS;
constexpr int K1_STAT = 16;
__device__ __forceinline__ uint32_t raw_box(uint32_t sbase, int i) {
    return i < K1_WGS ? sbase + i * WG_BYTES + O_RAW : sbase + O_XTRA + (i - K1_WGS) * 4096;
}
__device__ __forceinline__ void transpose_window(uint32_t sbase, int warp, int lane, int ch0) {
    const int ch = (lane >> 2) + ch0;
    const uint32_t ub = sbase + ch * WG_BYTES + (lane & 3) * 4;
#pragma unroll
    for (int k = 0; k < 4; k++) {
        const int gi = warp + k * (4 * K1_WGS);
        if (gi < 64) {
            const uint4 v = ldsm_x4_t(raw_box(sbase, gi >> 3) + (gi & 7) * 512 + lane * 16);
            if (ch >= 0 && ch < K1_WGS) {
                const uint32_t a0 = u_addr(ub, 4 * gi);
                sts32(a0, v.x);
                sts32(a0 ^ 16, v.y);
                sts32(a0 ^ 32, v.z);
                sts32(a0 ^ 48, v.w);
            }
        }
    }
}

__global__ void __launch_bounds__(128 * K1_WGS, 1)
ssm_kernel(const __grid_constant__ CUtensorMap tmc, const __grid_constant__ CUtensorMap tmo,
           const bf16* __restrict__ x, const bf16* __restrict__ gw, Params p) {
    extern __shared__ __align__(1024) uint8_t smem_raw[];
    const uint32_t sbase = smem_u32(smem_raw);
    const int tid = threadIdx.x, t = tid & 127, lane = tid & 31;
    const int wg = __shfl_sync(0xffffffffu, tid >> 7, 0), warp = __shfl_sync(0xffffffffu, tid >> 5, 0);
    const int d0 = blockIdx.x * K1_WGS, d = min(d0 + wg, D_MODEL - 1);
    const uint32_t sb = sbase + wg * WG_BYTES;
    const uint32_t xbar = sbase + WG_BYTES - 16;
    const int dw = d0 & ~7;
    const bool two = (d0 & 7) > 3 && dw + 8 < D_MODEL;
    DBG1(0);
    if (blockIdx.x == 0) {
        if (tid == 0) {
            g_epoch = g_epoch + 1;
            asm volatile("fence.acq_rel.gpu;" ::: "memory");
        }
        __syncthreads();
    }
    asm volatile("griddepcontrol.launch_dependents;");
    if (blockIdx.x >= K1_CTAS) {
        const uint32_t tag = (g_stat_epoch[blockIdx.x - K1_CTAS] + 1) & 1u;
        __syncthreads();
        if (tid == 0) g_stat_epoch[blockIdx.x - K1_CTAS] = g_stat_epoch[blockIdx.x - K1_CTAS] + 1;
        uint32_t gr[9];
#pragma unroll
        for (int i = 0; i < 9; i++) gr[i] = __ldg(reinterpret_cast<const uint32_t*>(gw) + lane + 32 * i);
#pragma unroll 1
        for (int row = (blockIdx.x - K1_CTAS) * (4 * K1_WGS) + warp; row < L_SEQ; row += 2 * K1_STAT * 4 * K1_WGS) {
            const int row2 = min(row + K1_STAT * 4 * K1_WGS, L_SEQ - 1);
            uint32_t xr[2][9];
#pragma unroll
            for (int i = 0; i < 9; i++) {
                xr[0][i] = __ldg(reinterpret_cast<const uint32_t*>(x + (size_t)row * D_MODEL) + lane + 32 * i);
                xr[1][i] = __ldg(reinterpret_cast<const uint32_t*>(x + (size_t)row2 * D_MODEL) + lane + 32 * i);
            }
#pragma unroll
            for (int h = 0; h < 2; h++) {
                float s = 0.f, gs = 0.f;
#pragma unroll
                for (int i = 0; i < 9; i++) {
                    s += bf_lo(xr[h][i]) + bf_hi(xr[h][i]);
                    const uint32_t pr = hmul2_bf(xr[h][i], gr[i]);
                    gs += bf_lo(pr) + bf_hi(pr);
                }
#pragma unroll
                for (int o = 16; o; o >>= 1) {
                    s += __shfl_xor_sync(~0u, s, o);
                    gs += __shfl_xor_sync(~0u, gs, o);
                }
                const float mean = s * (1.f / D_MODEL);
                float q = 0.f;
#pragma unroll
                for (int i = 0; i < 9; i++) {
                    const float a = bf_lo(xr[h][i]) - mean, b = bf_hi(xr[h][i]) - mean;
                    q = fmaf(a, a, fmaf(b, b, q));
                }
#pragma unroll
                for (int o = 16; o; o >>= 1) q += __shfl_xor_sync(~0u, q, o);
                if (lane == 0) {
                    const float var = bf16r(q * (1.f / D_MODEL));
                    const float den = bf16r(sqrtf(bf16r(var + 1e-5f)));
                    const int r = h ? row2 : row;
                    const unsigned long long e = ((unsigned long long)((__float_as_uint(__fdividef(1.f, den)) & ~1u) | tag) << 32) |
                                                 pack_bf16(mean, mean);
                    asm volatile("st.relaxed.gpu.global.b64 [%0], %1;" ::"l"(&g_rowstat[r]), "l"(e) : "memory");
                    g_gate[r] = bf16r(__fdividef(1.f, 1.f + __expf(-bf16r(gs))));
                }
            }
        }
        return;
    }
    if (tid == 0) {
        mbar_init(xbar, 1);
        asm volatile("fence.mbarrier_init.release.cluster;" ::: "memory");
        mbar_expect(xbar, 8 * 4096);
#pragma unroll
        for (int i = 0; i < 8; i++) tma2d(raw_box(sbase, i), &tmc, dw, i * 256, xbar);
    }
    const ModeIn mi = load_mode(p, d, t);
    sts128(sb + O_U + t * 16, 0, 0, 0, 0);
    sts128(sb + O_KN + t * 16, 0, 0, 0, 0);
    gen_powers(mi, sb, t);
    DBG1(1);
    asm volatile("fence.proxy.async.shared::cta;" ::: "memory");
    __syncthreads();
    float kd[16];
    WG_FENCE();
    KgenSteps<16>::run(kd, (sb & 0x3FFFF) >> 4);
    WG_COMMIT();
    mbar_wait(xbar, 0);
    DBG1(2);
    transpose_window(sbase, warp, lane, dw - d0);
    if (two) {
        asm volatile("fence.proxy.async.shared::cta;" ::: "memory");
        __syncthreads();
        if (tid == 0) {
            mbar_expect(xbar, 8 * 4096);
#pragma unroll
            for (int i = 0; i < 8; i++) tma2d(raw_box(sbase, i), &tmc, dw + 8, i * 256, xbar);
        }
    }
    DBG1(3);
    WG_WAIT(0);
#pragma unroll
    for (int i = 0; i < 16; i++) asm volatile("" : "+f"(kd[i])::"memory");
    build_tables(kd, mi.dsk, sb, t, 1 + wg);
    if (two) {
        mbar_wait(xbar, 1);
        transpose_window(sbase, warp, lane, dw + 8 - d0);
    }
    asm volatile("fence.proxy.async.shared::cta;" ::: "memory");
    __syncthreads();
    DBG1(5);
    build_windows(sb, t);
    wg_bar(1 + wg);
    DBG1(9);
    if (d0 + wg < D_MODEL) convolve(d, sb, t, 1 + wg, &tmo);
}
}

constexpr int XT_BYTES = 128 * D_MODEL * 2;
constexpr int STAGE_BYTES = 96 * 128;
constexpr int NSTAGE = 6;
constexpr int SM_STAGES = XT_BYTES;
constexpr int SM_BARS = SM_STAGES + NSTAGE * STAGE_BYTES;
constexpr int SM_B1 = SM_BARS + 512;
constexpr int SM_B2 = SM_B1 + 576 * 4;
constexpr int MLP_SMEM = SM_B2 + 576 * 2;
__host__ __device__ constexpr int red_buf(int c) { return c < 7 ? c * 18432 : SM_STAGES + (c - 7) * 18432; }
constexpr int BAR_FULL = 0, BAR_EMPTY = 48, BAR_X = 96, BAR_PARKFREE = 168, BAR_STORED = 176, BAR_LOADED = 248, BAR_A = 320;

__device__ __forceinline__ float gelu2(float x) {
    const float k0 = 0.7978845608028654f, k1 = 0.7978845608028654f * 0.044715f;
    float u = x * fmaf(x * x, k1, k0);
    float th;
    asm("tanh.approx.f32 %0, %1;" : "=f"(th) : "f"(u));
    return fmaf(x, th, x);
}

__device__ __forceinline__ void epi_gelu(const float (&acc)[32], int i, uint32_t b1_addr, float r0, float r1,
                                         uint32_t (&o)[4]) {
    float b0, b1, b2, b3;
    asm volatile("ld.shared.v4.f32 {%0,%1,%2,%3}, [%4];"
                 : "=f"(b0), "=f"(b1), "=f"(b2), "=f"(b3) : "r"(b1_addr + i * 16));
    o[0] = pack_bf16(gelu2(fmaf(acc[8 * i + 0], r0, b0)), gelu2(fmaf(acc[8 * i + 1], r0, b1)));
    o[1] = pack_bf16(gelu2(fmaf(acc[8 * i + 2], r1, b0)), gelu2(fmaf(acc[8 * i + 3], r1, b1)));
    o[2] = pack_bf16(gelu2(fmaf(acc[8 * i + 4], r0, b2)), gelu2(fmaf(acc[8 * i + 5], r0, b3)));
    o[3] = pack_bf16(gelu2(fmaf(acc[8 * i + 6], r1, b2)), gelu2(fmaf(acc[8 * i + 7], r1, b3)));
}
__device__ __forceinline__ void epi_park(const float (&acc)[32], int i, uint32_t b1_addr, uint32_t park_addr,
                                         float r0, float r1) {
    uint32_t o[4];
    epi_gelu(acc, i, b1_addr, r0, r1, o);
    asm volatile("st.shared.v4.b32 [%0], {%1,%2,%3,%4};" ::"r"(park_addr + i * 4096), "r"(o[0]), "r"(o[1]),
                 "r"(o[2]), "r"(o[3]) : "memory");
}
__device__ __forceinline__ void epi_part(const float (&acc)[32], int i, uint4* part, uint32_t par) {
    uint4 v;
    v.x = (pack_bf16(acc[8 * i + 0], acc[8 * i + 1]) & ~1u) | par;
    v.y = pack_bf16(acc[8 * i + 2], acc[8 * i + 3]);
    v.z = (pack_bf16(acc[8 * i + 4], acc[8 * i + 5]) & ~1u) | par;
    v.w = pack_bf16(acc[8 * i + 6], acc[8 * i + 7]);
    asm volatile("{\n.reg .b128 q;\nmov.b128 q, {%1, %2};\nst.relaxed.gpu.global.b128 [%0], q;\n}\n" ::"l"(part + i * 32),
                 "l"(((unsigned long long)v.y << 32) | v.x), "l"(((unsigned long long)v.w << 32) | v.z) : "memory");
}
__device__ __forceinline__ void warp_arrive(uint32_t bar, int lane) {
    __syncwarp();
    if (lane == 0) asm volatile("mbarrier.arrive.shared::cta.b64 _, [%0];" ::"r"(bar) : "memory");
}

__device__ __forceinline__ void probe_partials(const uint4* unit, uint32_t par) {
    asm volatile(
        "{\n.reg .pred p;\n.reg .u32 n, v;\nmov.u32 n, 0;\n"
        "PROBE_LOOP:\n"
        "ld.relaxed.gpu.global.u32 v, [%0];\n"
        "xor.b32 v, v, %1;\n"
        "and.b32 v, v, 1;\n"
        "setp.ne.u32 p, v, 0;\n"
        "vote.sync.any.pred p, p, 0xffffffff;\n"
        "@!p bra PROBE_DONE;\n"
        "add.u32 n, n, 1;\n"
        "setp.lt.u32 p, n, 1048576;\n"
        "@p bra PROBE_LOOP;\n"
        "trap;\n"
        "PROBE_DONE:\n}\n" ::"l"(unit), "r"(par) : "memory");
}

template <int EPI>
__device__ __forceinline__ void run_chunk(float (&cur)[32], float (&prev)[32], const uint32_t (&af)[NAF][4],
                                          int parity, uint32_t bars, uint32_t desc0, uint32_t adesc0, uint32_t p0, uint32_t p1,
                                          uint4* part, bool sig, uint32_t rbar, int lane, float r0, float r1) {
#pragma unroll
    for (int s = 0; s < 6; s++) {
        mbar_wait(bars + BAR_FULL + s * 8, parity);
        WG_FENCE();
        mma_stage_rt(s, cur, af, desc0, adesc0);
        WG_COMMIT();
        if (s >= 1 && s <= 4) {
            if (EPI == 1) epi_park(prev, s - 1, p0, p1, r0, r1);
            if (EPI == 2) epi_part(prev, s - 1, part, p1);
        }
        if (s == 4 && EPI == 2) warp_arrive(p0, lane);
        WG_WAIT(1);
        if (sig) asm volatile("mbarrier.arrive.shared::cluster.b64 _, [%0];" ::"r"(rbar + ((s + 5) % 6) * 8) : "memory");
        if (s == 0) fence_acc(prev);
    }
}

__global__ void __cluster_dims__(2, 1, 1) __launch_bounds__(384, 1)
mlp_kernel(const __grid_constant__ CUtensorMap tmx, const __grid_constant__ CUtensorMap tmw1,
           const __grid_constant__ CUtensorMap tmw2, const __grid_constant__ CUtensorMap tma,
           const bf16* __restrict__ b1, const bf16* __restrict__ b2,
           bf16* __restrict__ out) {
    extern __shared__ __align__(1024) uint8_t smem_raw[];
    const uint32_t sbase = smem_u32(smem_raw);
    uint8_t* sgen = smem_raw;
    const int tid = threadIdx.x, lane = tid & 31;
    const int warp = __shfl_sync(0xffffffffu, tid >> 5, 0);
    const int wgid = __shfl_sync(0xffffffffu, tid >> 7, 0);
    const int m = blockIdx.x & 15, f = blockIdx.x >> 4;
    const uint32_t rank = m & 1;
    const uint32_t bars = sbase + SM_BARS;
    if (warp == 0) DBG(12);

    if (tid == 0) {
        if (sbase & 1023) asm volatile("trap;");
        for (int i = 0; i < NSTAGE; i++) {
            mbar_init(bars + BAR_FULL + i * 8, 1);
            mbar_init(bars + BAR_EMPTY + i * 8, 4);
        }
        for (int i = 0; i < 9; i++) mbar_init(bars + BAR_X + i * 8, 1);
        mbar_init(bars + BAR_PARKFREE, 8);
        mbar_init(bars + BAR_A, 1);
        for (int i = 0; i < 9; i++) {
            mbar_init(bars + BAR_STORED + i * 8, 8);
            mbar_init(bars + BAR_LOADED + i * 8, 1);
        }
        asm volatile("fence.mbarrier_init.release.cluster;" ::: "memory");
        for (int j = 0; j < 3; j++) {
            mbar_expect(bars + BAR_X + j * 8, 16384);
            tma2d(sbase + j * 16384, &tmx, j * 64, m * 128, bars + BAR_X + j * 8);
        }
    }
    uint32_t b1v0 = 0, b1v1 = 0;
    if (wgid < 2) {
        const uint32_t* b1w = reinterpret_cast<const uint32_t*>(b1 + f * 576);
        b1v0 = __ldg(b1w + (tid >> 5) * 32 + (tid & 7) * 4 + ((tid >> 3) & 3));
        if (tid < 32) b1v1 = __ldg(b1w + 8 * 32 + (tid & 7) * 4 + ((tid >> 3) & 3));
    }
    __syncthreads();
    asm volatile("barrier.cluster.arrive.relaxed.aligned;\nbarrier.cluster.wait.aligned;" ::: "memory");

    if (warp == 0) DBG(0);
    if (wgid == 2) {
        asm volatile("setmaxnreg.dec.sync.aligned.u32 40;");
        if (warp == 8) {
            if (lane == 0) {
                const uint32_t dst0 = sbase + SM_STAGES + rank * (STAGE_BYTES / 2);
#pragma unroll 1
                for (int cc = 0; cc < 18; cc++) {
                    const CUtensorMap* tm = cc < 9 ? &tmw1 : &tmw2;
                    const int c0 = cc < 9 ? f * 576 + cc * 64 : (cc - 9) * 64;
                    const int c1 = (cc < 9 ? 0 : f * 576) + rank * 48;
                    const int par = (cc & 1) ^ 1;
#pragma unroll
                    for (int s = 0; s < 6; s++) {
                        mbar_wait(bars + BAR_EMPTY + s * 8, par);
                        mbar_expect(bars + BAR_FULL + s * 8, STAGE_BYTES);
                        tma2d_mc(dst0 + s * STAGE_BYTES, tm, c0, c1 + s * 96, bars + BAR_FULL + s * 8, 3);
                        if (cc == 0 && s >= 1 && s <= 3) {
#pragma unroll
                            for (int j = 2 * s + 1; j < 2 * s + 3; j++) {
                                mbar_expect(bars + BAR_X + j * 8, 16384);
                                tma2d(sbase + j * 16384, &tmx, j * 64, m * 128, bars + BAR_X + j * 8);
                            }
                        }
                    }
                }
            }
        } else if (warp == 9) {
            {
                uint32_t* b2s = reinterpret_cast<uint32_t*>(sgen + SM_B2);
                for (int w = lane; w < 288; w += 32) {
                    const int jj = w & 1, q = (w >> 1) & 3, ci = w >> 3;
                    b2s[w] = __ldg(reinterpret_cast<const uint32_t*>(b2) + ci * 8 + jj * 4 + q);
                }
                __syncwarp();
            }
            asm volatile("griddepcontrol.wait;" ::: "memory");
            const uint32_t par = __ldcg(&g_epoch);
            mbar_wait(bars + BAR_PARKFREE, 0);
            asm volatile("fence.proxy.async.shared::cta;" ::: "memory");
            const uint4* psrc = g_part + (m * 9 * 8 + f) * (8 * 4 * 32);
#pragma unroll 1
            for (int c = 0; c < 8; c++) {
                const uint32_t buf = sbase + red_buf(c);
                if (c == 7) {
                    mbar_wait(bars + BAR_EMPTY + 0, 1);
                    mbar_wait(bars + BAR_EMPTY + 8, 1);
                    mbar_wait(bars + BAR_EMPTY + 16, 1);
                }
                if (lane == 0) {
                    mbar_expect(bars + BAR_LOADED + c * 8, c < 8 ? 16384 + 2048 : 2048);
                    tma2d(buf + 16384, &tma, m * 128 + f * 16, c * 64, bars + BAR_LOADED + c * 8);
                    if (c == 7) {
                        mbar_expect(bars + BAR_LOADED + 64, 2048);
                        tma2d(sbase + red_buf(8) + 16384, &tma, m * 128 + f * 16, 8 * 64, bars + BAR_LOADED + 64);
                    }
                }
                mbar_wait(bars + BAR_STORED + c * 8, 0);
                probe_partials(psrc + (lane & 7) * 128 + 96 + 31, par);
                DBG(16 + c);
                if (lane == 0)
                    asm volatile("cp.async.bulk.shared::cluster.global.mbarrier::complete_tx::bytes [%0], [%1], 16384, [%2];"
                                 ::"r"(buf), "l"(psrc), "r"(bars + BAR_LOADED + c * 8) : "memory");
                psrc += 8 * 8 * 4 * 32;
            }
        }
        __syncwarp();
        asm volatile("barrier.cluster.arrive.relaxed.aligned;\nbarrier.cluster.wait.aligned;" ::: "memory");
    } else {
        asm volatile("setmaxnreg.inc.sync.aligned.u32 232;");
        const uint32_t par = __ldcg(&g_epoch) & 1u;
        uint2 rs0, rs1;
        {
            const uint2* rp = &g_rowstat[m * 128 + warp * 16 + (lane >> 2)];
            int tries = 0;
            while (true) {
                unsigned long long e0, e1;
                asm volatile("ld.relaxed.gpu.global.b64 %0, [%1];" : "=l"(e0) : "l"(rp) : "memory");
                asm volatile("ld.relaxed.gpu.global.b64 %0, [%1];" : "=l"(e1) : "l"(rp + 8) : "memory");
                rs0 = make_uint2((uint32_t)e0, (uint32_t)(e0 >> 32));
                rs1 = make_uint2((uint32_t)e1, (uint32_t)(e1 >> 32));
                if (!__any_sync(0xffffffffu, ((rs0.y ^ par) | (rs1.y ^ par)) & 1)) break;
                if (++tries > (1 << 22)) asm volatile("trap;");
            }
        }
        const int g = lane >> 2, tq = lane & 3;
        uint32_t af[NAF][4];
        float acc0[32], acc1[32];
        const bool sig = (tid & 127) < 2;
        uint32_t rbar;
        asm volatile("mapa.shared::cluster.u32 %0, %1, %2;" : "=r"(rbar) : "r"(bars + BAR_EMPTY), "r"(tid & 1));
        const uint32_t desc0 = ((sbase + SM_STAGES) & 0x3FFFF) >> 4;
        const uint32_t adesc0 = ((sbase + 8 * 16384 + wgid * 8192) & 0x3FFFF) >> 4;

        {
            float2* b1s = reinterpret_cast<float2*>(sgen + SM_B1);
            b1s[tid] = make_float2(bf_lo(b1v0), bf_hi(b1v0));
            if (tid < 32) b1s[256 + tid] = make_float2(bf_lo(b1v1), bf_hi(b1v1));
        }
        const float rstd0 = __uint_as_float(rs0.y), rstd1 = __uint_as_float(rs1.y);
        {
            const int lrow = warp * 16 + (lane & 7) + ((lane >> 3) & 1) * 8;
            const uint32_t rbase = sbase + lrow * 128;
            const int hi = lane >> 4, sw = lrow & 7;
#pragma unroll
            for (int s = 0; s < 6; s++) {
#pragma unroll
                for (int k = s * 6; k < s * 6 + 6; k++) {
                    const int j = k >> 2, kk = k & 3;
                    if (kk == 0 || k == s * 6) mbar_wait(bars + BAR_X + j * 8, 0);
                    uint32_t tmp[4];
                    uint32_t (&a)[4] = (k < NAF) ? af[(k < NAF) ? k : 0] : tmp;
                    const uint32_t addr = rbase + j * 16384 + (((kk * 2 + hi) ^ sw) << 4);
                    ldsm_x4(a, addr);
                    a[0] = hsub2_bf(a[0], rs0.x);
                    a[1] = hsub2_bf(a[1], rs1.x);
                    a[2] = hsub2_bf(a[2], rs0.x);
                    a[3] = hsub2_bf(a[3], rs1.x);
                    if (k >= NAF) stsm_x4(a, addr);
                }
                if (s == 5) {
                    asm volatile("fence.proxy.async.shared::cta;" ::: "memory");
                    asm volatile("bar.sync %0, 128;" ::"r"(3 + wgid) : "memory");
                    if (warp == 0) DBG(1);
                }
                mbar_wait(bars + BAR_FULL + s * 8, 0);
                WG_FENCE();
                mma_stage_rt(s, acc0, af, desc0, adesc0);
                WG_COMMIT();
                if (s > 0) {
                    WG_WAIT(1);
                    if (sig) asm volatile("mbarrier.arrive.shared::cluster.b64 _, [%0];" ::"r"(rbar + (s - 1) * 8) : "memory");
                }
            }
            asm volatile("bar.sync 1, 256;" ::: "memory");
        }
        {
            uint32_t b1a = sbase + SM_B1 + tq * 64, park = sbase + tid * 16;
#pragma unroll 1
            for (int c = 1; c < 9; c += 2) {
                if (warp == 0) DBG(2 + (c >> 1));
                run_chunk<1>(acc1, acc0, af, 1, bars, desc0, adesc0, b1a, park, nullptr, sig, rbar, lane, rstd0, rstd1);
                run_chunk<1>(acc0, acc1, af, 0, bars, desc0, adesc0, b1a + 256, park + 16384, nullptr, sig, rbar, lane, rstd0, rstd1);
                b1a += 512;
                park += 32768;
            }
        }
        if (warp == 0) DBG(6);
        WG_WAIT(0);
        if (sig) asm volatile("mbarrier.arrive.shared::cluster.b64 _, [%0];" ::"r"(rbar + 5 * 8) : "memory");
        fence_acc(acc0);
#pragma unroll
        for (int k = 0; k < 32; k++)
            asm volatile("ld.shared.v4.b32 {%0,%1,%2,%3}, [%4];"
                         : "=r"(af[k][0]), "=r"(af[k][1]), "=r"(af[k][2]), "=r"(af[k][3])
                         : "r"(sbase + tid * 16 + k * 4096) : "memory");
        {
#pragma unroll
            for (int s = 0; s < 6; s++) {
                mbar_wait(bars + BAR_FULL + s * 8, 1);
                WG_FENCE();
                mma_stage_rt(s, acc1, af, desc0, adesc0);
                WG_COMMIT();
                if (s < 2) epi_gelu(acc0, s, sbase + SM_B1 + tq * 64 + 8 * 256, rstd0, rstd1, af[32 + (s & 1)]);
                if (s == 2 || s == 3) {
                    uint32_t tmp[4];
                    epi_gelu(acc0, s, sbase + SM_B1 + tq * 64 + 8 * 256, rstd0, rstd1, tmp);
                    const int lrow = warp * 16 + (lane & 7) + ((lane >> 3) & 1) * 8;
                    stsm_x4(tmp, sbase + 8 * 16384 + lrow * 128 + (((s * 2 + (lane >> 4)) ^ (lrow & 7)) << 4));
                }
                if (s == 3) {
                    asm volatile("fence.proxy.async.shared::cta;" ::: "memory");
                    asm volatile("bar.sync %0, 128;" ::"r"(3 + wgid) : "memory");
                }
                if (s > 0) {
                    WG_WAIT(1);
                    if (sig) asm volatile("mbarrier.arrive.shared::cluster.b64 _, [%0];" ::"r"(rbar + (s - 1) * 8) : "memory");
                }
                if (s == 5) warp_arrive(bars + BAR_PARKFREE, lane);
            }
        }
        uint4* part = g_part + (size_t)((m * 9 * 8 + warp) * 8 + f) * (4 * 32) + lane;
        uint32_t stored = bars + BAR_STORED;
#pragma unroll 1
        for (int c = 1; c < 9; c += 2) {
            if (warp == 0) DBG(7 + (c >> 1));
            run_chunk<2>(acc0, acc1, af, 0, bars, desc0, adesc0, stored, par, part, sig, rbar, lane, 0.f, 0.f);
            run_chunk<2>(acc1, acc0, af, 1, bars, desc0, adesc0, stored + 8, par, part + 8 * 8 * 4 * 32, sig, rbar, lane, 0.f, 0.f);
            part += 2 * 8 * 8 * 4 * 32;
            stored += 16;
        }
        const int t0 = m * 128 + f * 16 + g;
        asm volatile("griddepcontrol.wait;" ::: "memory");
        const float g0 = __ldcg(&g_gate[t0]), g1 = __ldcg(&g_gate[t0 + 8]);
        WG_WAIT(0);
        fence_acc(acc1);
#pragma unroll
        for (int i = 0; i < 4; i++) epi_part(acc1, i, part, par);
        asm volatile("barrier.cluster.arrive.relaxed.aligned;" ::: "memory");
        if (warp == 0) DBG(11);
        {
            const uint32_t gA = pack_bf16(g0, g0), gB = pack_bf16(g1, g1);
            const uint32_t half2 = 0x3f003f00u, one2 = 0x3f803f80u;
            const uint32_t oA = hsub2_bf(one2, gA), oB = hsub2_bf(one2, gB);
            uint32_t* o32 = reinterpret_cast<uint32_t*>(out + (size_t)t0 * D_MODEL + 2 * tq) + warp * 4;
            const uint32_t lm = sbase + 16384 + (lane & 7) * 32 + ((lane >> 3) & 1) * 16 + warp * 256;
            const uint32_t a0 = sbase + (warp >> 1) * 512 + lane * 16 + (warp & 1) * 8;
            const uint32_t b2a = sbase + SM_B2 + (warp >> 1) * 32 + tq * 8 + (warp & 1) * 4;
            const uint2* ps0 = reinterpret_cast<const uint2*>(
                g_part + (m * 9 * 8 + f) * (8 * 4 * 32) + (warp >> 1) * 32 + lane) + (warp & 1);
#pragma unroll 1
            for (int c0 = 0; c0 < 10; c0 += 2) {
                const bool last = c0 == 8;
                uint2 v[2][8], av[2];
                uint32_t bb[2], bad = 0;
#pragma unroll
                for (int k = 0; k < 2; k++) {
                    const int c = last ? 8 : c0 + k;
                    const uint32_t bo = red_buf(c);
                    mbar_wait(bars + BAR_LOADED + c * 8, 0);
#pragma unroll
                    for (int q = 0; q < 8; q++) {
                        v[k][q] = ssm::lds64(a0 + bo + q * 2048);
                        bad |= v[k][q].x ^ par;
                    }
                    asm volatile("ldmatrix.sync.aligned.m8n8.x2.trans.shared.b16 {%0,%1}, [%2];"
                                 : "=r"(av[k].x), "=r"(av[k].y) : "r"(lm + bo) : "memory");
                    bb[k] = ssm::lds32(b2a + c * 128);
                }
                if (last) {
                    bad = 1;
                    probe_partials(g_part + ((m * 9 + 8) * 8 + f) * (8 * 4 * 32) + (lane & 7) * 128 + (warp >> 1) * 32 + 31, par);
                }
                int tries = 0;
                while (__any_sync(0xffffffffu, bad & 1)) {
                    bad = 0;
#pragma unroll
                    for (int k = 0; k < 2; k++)
#pragma unroll
                        for (int q = 0; q < 8; q++) {
                            unsigned long long w;
                            asm volatile("ld.relaxed.gpu.global.b64 %0, [%1];" : "=l"(w)
                                         : "l"(ps0 + (last ? 8 : c0 + k) * (8 * 8 * 4 * 32 * 2) + q * 256) : "memory");
                            v[k][q] = make_uint2((uint32_t)w, (uint32_t)(w >> 32));
                            bad |= v[k][q].x ^ par;
                        }
                    if (++tries > (1 << 20)) asm volatile("trap;");
                }
#pragma unroll
                for (int k = 0; k < 2; k++) {
                    const int c = last ? 8 : c0 + k;
                    float sx0 = 0.f, sx1 = 0.f, sy0 = 0.f, sy1 = 0.f;
#pragma unroll
                    for (int q = 0; q < 8; q++) {
                        sx0 += bf_lo(v[k][q].x); sx1 += bf_hi(v[k][q].x);
                        sy0 += bf_lo(v[k][q].y); sy1 += bf_hi(v[k][q].y);
                    }
                    o32[c * 32] = hadd2_bf(hmul2_bf(gA, av[k].x), hmul2_bf(oA, hfma2_bf(pack_bf16(sx0, sx1), half2, bb[k])));
                    o32[c * 32 + 4 * D_MODEL] =
                        hadd2_bf(hmul2_bf(gB, av[k].y), hmul2_bf(oB, hfma2_bf(pack_bf16(sy0, sy1), half2, bb[k])));
                }
                if (warp == 0 && c0 >= 4) DBG(30 + c0 / 2);
            }
        }
        asm volatile("barrier.cluster.wait.aligned;" ::: "memory");
        if (warp == 0) DBG(13);
    }
}

typedef CUresult (*EncodeFn)(CUtensorMap*, CUtensorMapDataType, cuuint32_t, void*, const cuuint64_t*,
                             const cuuint64_t*, const cuuint32_t*, const cuuint32_t*, CUtensorMapInterleave,
                             CUtensorMapSwizzle, CUtensorMapL2promotion, CUtensorMapFloatOOBfill);

static void make_map(EncodeFn enc, CUtensorMap* m, const void* ptr, uint64_t cols, uint64_t rows, uint32_t box_c,
                     uint32_t box_r, CUtensorMapSwizzle swz = CU_TENSOR_MAP_SWIZZLE_128B) {
    cuuint64_t dim[2] = {cols, rows};
    cuuint64_t str[1] = {cols * 2};
    cuuint32_t box[2] = {box_c, box_r};
    cuuint32_t es[2] = {1, 1};
    enc(m, CU_TENSOR_MAP_DATA_TYPE_BFLOAT16, 2, const_cast<void*>(ptr), dim, str, box, es,
        CU_TENSOR_MAP_INTERLEAVE_NONE, swz, CU_TENSOR_MAP_L2_PROMOTION_L2_128B,
        CU_TENSOR_MAP_FLOAT_OOB_FILL_NONE);
}

}

extern "C" void kernel_launch(void* const* d_in, const int* in_sizes, int n_in, void* d_out, int out_size) {
    const bf16* u = (const bf16*)d_in[0];
    const bf16* A_re = (const bf16*)d_in[1];
    const bf16* A_im = (const bf16*)d_in[2];
    const bf16* B_re = (const bf16*)d_in[3];
    const bf16* B_im = (const bf16*)d_in[4];
    const bf16* C_re = (const bf16*)d_in[5];
    const bf16* C_im = (const bf16*)d_in[6];
    const bf16* log_dt = (const bf16*)d_in[7];
    const bf16* Dskip = (const bf16*)d_in[8];
    const bf16* w1 = (const bf16*)d_in[10];
    const bf16* b1 = (const bf16*)d_in[11];
    const bf16* w2 = (const bf16*)d_in[12];
    const bf16* b2 = (const bf16*)d_in[13];
    const bf16* gw = (const bf16*)d_in[14];
    bf16* out = (bf16*)d_out;

    static EncodeFn enc = nullptr;
    if (!enc) {
        void* fn = nullptr;
        cudaDriverEntryPointQueryResult q;
        cudaGetDriverEntryPoint("cuTensorMapEncodeTiled", &fn, cudaEnableDefault, &q);
        enc = (EncodeFn)fn;
        cudaFuncSetAttribute(mlp_kernel, cudaFuncAttributeMaxDynamicSharedMemorySize, MLP_SMEM);
        cudaFuncSetAttribute(ssm::ssm_kernel, cudaFuncAttributeMaxDynamicSharedMemorySize, ssm::K1_SMEM);
    }
    static void* aT_ptr = nullptr;
    if (!aT_ptr) cudaGetSymbolAddress(&aT_ptr, g_aT);
    CUtensorMap tmx, tmw1, tmw2, tma;
    make_map(enc, &tma, aT_ptr, L_SEQ, D_MODEL, 16, 64, CU_TENSOR_MAP_SWIZZLE_NONE);
    make_map(enc, &tmx, u, D_MODEL, L_SEQ, 64, 128);
    make_map(enc, &tmw1, w1, F_DIM, D_MODEL, 64, 48);
    make_map(enc, &tmw2, w2, D_MODEL, F_DIM, 64, 48);

    cudaStream_t st = cudaStreamPerThread;
    ssm::Params sp{A_re, A_im, B_re, B_im, C_re, C_im, log_dt, Dskip};
    CUtensorMap tmc, tmo;
    make_map(enc, &tmc, u, D_MODEL, L_SEQ, 8, 256, CU_TENSOR_MAP_SWIZZLE_NONE);
    make_map(enc, &tmo, aT_ptr, 64, D_MODEL * 32, 64, 32);
    ssm::ssm_kernel<<<ssm::K1_CTAS + ssm::K1_STAT, 128 * ssm::K1_WGS, ssm::K1_SMEM, st>>>(tmc, tmo, u, gw, sp);
    cudaLaunchConfig_t cfg = {};
    cfg.gridDim = dim3(128);
    cfg.blockDim = dim3(384);
    cfg.dynamicSmemBytes = MLP_SMEM;
    cfg.stream = st;
    cudaLaunchAttribute at[1];
    at[0].id = cudaLaunchAttributeProgrammaticStreamSerialization;
    at[0].val.programmaticStreamSerializationAllowed = 1;
    cfg.attrs = at;
    cfg.numAttrs = 1;
    cudaLaunchKernelEx(&cfg, mlp_kernel, tmx, tmw1, tmw2, tma, b1, b2, out);
}
```

```cpp
#include <cuda_runtime.h>
#include <cuda_bf16.h>
#include <cuda.h>
#include <stdint.h>

namespace {

constexpr int L_SEQ = 2048;
constexpr int D_MODEL = 576;
constexpr int F_DIM = 4608;
constexpr int N_MODES = 128;

typedef __nv_bfloat16 bf16;

__device__ uint2 g_rowstat[L_SEQ];
__device__ float g_gate[L_SEQ];
__device__ bf16 g_aT[D_MODEL * L_SEQ];
__device__ uint4 g_part[16 * 9 * 8 * 8 * 4 * 32];
__device__ unsigned g_stat_epoch[16];
__device__ unsigned g_epoch;

#define DBG(slot)
#define DBG1(slot)

__device__ __forceinline__ uint32_t smem_u32(const void* p) { return (uint32_t)__cvta_generic_to_shared(p); }
__device__ __forceinline__ float bf16r(float x) { return __bfloat162float(__float2bfloat16_rn(x)); }
__device__ __forceinline__ uint32_t pack_bf16(float lo, float hi) {
    uint32_t r;
    asm("cvt.rn.bf16x2.f32 %0, %1, %2;" : "=r"(r) : "f"(hi), "f"(lo));
    return r;
}
__device__ __forceinline__ float bf_lo(uint32_t v) { return __uint_as_float(v << 16); }
__device__ __forceinline__ float bf_hi(uint32_t v) { return __uint_as_float(v & 0xffff0000u); }

__device__ __forceinline__ void mbar_init(uint32_t bar, int cnt) {
    asm volatile("mbarrier.init.shared::cta.b64 [%0], %1;" ::"r"(bar), "r"(cnt));
}
__device__ __forceinline__ void mbar_expect(uint32_t bar, int bytes) {
    asm volatile("mbarrier.arrive.expect_tx.shared::cta.b64 _, [%0], %1;" ::"r"(bar), "r"(bytes) : "memory");
}
__device__ __forceinline__ void mbar_wait(uint32_t bar, int parity) {
    asm volatile(
        "{\n.reg .pred p;\n.reg .u32 n;\nmov.u32 n, 0;\n"
        "WAIT_LOOP:\n"
        "mbarrier.try_wait.parity.shared::cta.b64 p, [%0], %1;\n"
        "@p bra WAIT_DONE;\n"
        "add.u32 n, n, 1;\n"
        "setp.lt.u32 p, n, 4194304;\n"
        "@p bra WAIT_LOOP;\n"
        "trap;\n"
        "WAIT_DONE:\n}\n" ::"r"(bar), "r"(parity) : "memory");
}
__device__ __forceinline__ void tma2d(uint32_t dst, const CUtensorMap* m, int c0, int c1, uint32_t bar) {
    asm volatile(
        "cp.async.bulk.tensor.2d.shared::cluster.global.mbarrier::complete_tx::bytes [%0], [%1, {%3,%4}], [%2];"
        ::"r"(dst), "l"(m), "r"(bar), "r"(c0), "r"(c1) : "memory");
}
__device__ __forceinline__ void tma2d_mc(uint32_t dst, const CUtensorMap* m, int c0, int c1, uint32_t bar,
                                         uint16_t mask) {
    asm volatile(
        "cp.async.bulk.tensor.2d.shared::cluster.global.mbarrier::complete_tx::bytes.multicast::cluster.L2::cache_hint "
        "[%0], [%1, {%3,%4}], [%2], %5, %6;"
        ::"r"(dst), "l"(m), "r"(bar), "r"(c0), "r"(c1), "h"(mask), "l"(0x12F0000000000000ull) : "memory");
}
__device__ __forceinline__ void ldsm_x4(uint32_t (&r)[4], uint32_t addr) {
    asm volatile("ldmatrix.sync.aligned.m8n8.x4.shared.b16 {%0,%1,%2,%3}, [%4];"
                 : "=r"(r[0]), "=r"(r[1]), "=r"(r[2]), "=r"(r[3]) : "r"(addr) : "memory");
}
#define WG_FENCE() asm volatile("wgmma.fence.sync.aligned;\n" ::: "memory")
#define WG_COMMIT() asm volatile("wgmma.commit_group.sync.aligned;\n" ::: "memory")
#define WG_WAIT(n) asm volatile("wgmma.wait_group.sync.aligned %0;\n" ::"n"(n) : "memory")

template <int SCALE_D, int OFF>
__device__ __forceinline__ void wgmma_rs_n64(float (&d)[32], const uint32_t (&a)[4], uint32_t desc_lo) {
    asm volatile(
        "{\n.reg .pred p;\n.reg .b32 lo;\n.reg .b64 dsc;\nsetp.ne.b32 p, %37, 0;\n"
        "add.u32 lo, %36, %38;\nmov.b64 dsc, {lo, 0x40000040};\n"
        "wgmma.mma_async.sync.aligned.m64n64k16.f32.bf16.bf16 "
        "{%0,%1,%2,%3,%4,%5,%6,%7,%8,%9,%10,%11,%12,%13,%14,%15,%16,%17,%18,%19,%20,%21,%22,%23,%24,%25,%26,%27,%28,%29,%30,%31},"
        "{%32,%33,%34,%35}, dsc, p, 1, 1, 1;\n}\n"
        : "+f"(d[0]), "+f"(d[1]), "+f"(d[2]), "+f"(d[3]), "+f"(d[4]), "+f"(d[5]), "+f"(d[6]), "+f"(d[7]),
          "+f"(d[8]), "+f"(d[9]), "+f"(d[10]), "+f"(d[11]), "+f"(d[12]), "+f"(d[13]), "+f"(d[14]), "+f"(d[15]),
          "+f"(d[16]), "+f"(d[17]), "+f"(d[18]), "+f"(d[19]), "+f"(d[20]), "+f"(d[21]), "+f"(d[22]), "+f"(d[23]),
          "+f"(d[24]), "+f"(d[25]), "+f"(d[26]), "+f"(d[27]), "+f"(d[28]), "+f"(d[29]), "+f"(d[30]), "+f"(d[31])
        : "r"(a[0]), "r"(a[1]), "r"(a[2]), "r"(a[3]), "r"(desc_lo), "n"(SCALE_D), "n"(OFF));
}
template <int OFF, int AOFF>
__device__ __forceinline__ void wgmma_ss_n64(float (&d)[32], uint32_t adesc_lo, uint32_t desc_lo) {
    asm volatile(
        "{\n.reg .pred p;\n.reg .b32 lo;\n.reg .b64 dsc, dsa;\nsetp.ne.b32 p, 1, 0;\n"
        "add.u32 lo, %33, %34;\nmov.b64 dsc, {lo, 0x40000040};\n"
        "add.u32 lo, %32, %35;\nmov.b64 dsa, {lo, 0x40000040};\n"
        "wgmma.mma_async.sync.aligned.m64n64k16.f32.bf16.bf16 "
        "{%0,%1,%2,%3,%4,%5,%6,%7,%8,%9,%10,%11,%12,%13,%14,%15,%16,%17,%18,%19,%20,%21,%22,%23,%24,%25,%26,%27,%28,%29,%30,%31},"
        "dsa, dsc, p, 1, 1, 0, 1;\n}\n"
        : "+f"(d[0]), "+f"(d[1]), "+f"(d[2]), "+f"(d[3]), "+f"(d[4]), "+f"(d[5]), "+f"(d[6]), "+f"(d[7]),
          "+f"(d[8]), "+f"(d[9]), "+f"(d[10]), "+f"(d[11]), "+f"(d[12]), "+f"(d[13]), "+f"(d[14]), "+f"(d[15]),
          "+f"(d[16]), "+f"(d[17]), "+f"(d[18]), "+f"(d[19]), "+f"(d[20]), "+f"(d[21]), "+f"(d[22]), "+f"(d[23]),
          "+f"(d[24]), "+f"(d[25]), "+f"(d[26]), "+f"(d[27]), "+f"(d[28]), "+f"(d[29]), "+f"(d[30]), "+f"(d[31])
        : "r"(adesc_lo), "r"(desc_lo), "n"(OFF), "n"(AOFF));
}
constexpr int NAF = 34;
template <int S, int FIRST>
__device__ __forceinline__ void mma_stage(float (&d)[32], const uint32_t (&af)[NAF][4], uint32_t desc_lo,
                                          uint32_t adesc_lo) {
    constexpr int B = (S * 96 * 128) >> 4;
    wgmma_rs_n64<FIRST ? 0 : 1, B + 0 * 128>(d, af[S * 6 + 0], desc_lo);
    wgmma_rs_n64<1, B + 1 * 128>(d, af[S * 6 + 1], desc_lo);
    wgmma_rs_n64<1, B + 2 * 128>(d, af[S * 6 + 2], desc_lo);
    wgmma_rs_n64<1, B + 3 * 128>(d, af[S * 6 + 3], desc_lo);
    if constexpr (S < 5) {
        wgmma_rs_n64<1, B + 4 * 128>(d, af[S * 6 + 4], desc_lo);
        wgmma_rs_n64<1, B + 5 * 128>(d, af[S * 6 + 5], desc_lo);
    } else {
        wgmma_ss_n64<B + 4 * 128, 4>(d, adesc_lo, desc_lo);
        wgmma_ss_n64<B + 5 * 128, 6>(d, adesc_lo, desc_lo);
    }
}
__device__ __forceinline__ void mma_stage_rt(int s, float (&d)[32], const uint32_t (&af)[NAF][4], uint32_t desc_lo,
                                             uint32_t adesc_lo) {
    if (s == 0) mma_stage<0, 1>(d, af, desc_lo, adesc_lo);
    if (s == 1) mma_stage<1, 0>(d, af, desc_lo, adesc_lo);
    if (s == 2) mma_stage<2, 0>(d, af, desc_lo, adesc_lo);
    if (s == 3) mma_stage<3, 0>(d, af, desc_lo, adesc_lo);
    if (s == 4) mma_stage<4, 0>(d, af, desc_lo, adesc_lo);
    if (s == 5) mma_stage<5, 0>(d, af, desc_lo, adesc_lo);
}
__device__ __forceinline__ void stsm_x4(const uint32_t (&r)[4], uint32_t addr) {
    asm volatile("stmatrix.sync.aligned.m8n8.x4.shared.b16 [%4], {%0,%1,%2,%3};"
                 ::"r"(r[0]), "r"(r[1]), "r"(r[2]), "r"(r[3]), "r"(addr) : "memory");
}
__device__ __forceinline__ void fence_acc(float (&d)[32]) {
#pragma unroll
    for (int i = 0; i < 32; i++) asm volatile("" : "+f"(d[i])::"memory");
}

__device__ __forceinline__ uint32_t hadd2_bf(uint32_t a, uint32_t b) {
    uint32_t r;
    asm("add.rn.bf16x2 %0, %1, %2;" : "=r"(r) : "r"(a), "r"(b));
    return r;
}
__device__ __forceinline__ uint32_t hsub2_bf(uint32_t a, uint32_t b) {
    uint32_t r;
    asm("sub.rn.bf16x2 %0, %1, %2;" : "=r"(r) : "r"(a), "r"(b));
    return r;
}
__device__ __forceinline__ uint32_t hmul2_bf(uint32_t a, uint32_t b) {
    uint32_t r;
    asm("mul.rn.bf16x2 %0, %1, %2;" : "=r"(r) : "r"(a), "r"(b));
    return r;
}
__device__ __forceinline__ uint32_t hfma2_bf(uint32_t a, uint32_t b, uint32_t c) {
    uint32_t r;
    asm("fma.rn.bf16x2 %0, %1, %2, %3;" : "=r"(r) : "r"(a), "r"(b), "r"(c));
    return r;
}
namespace ssm {
constexpr int O_H = 0;
constexpr int O_L = 12288;
constexpr int HL_END = O_L + 16384;
constexpr int O_Q = 0;
constexpr int O_Q12 = 5120;
constexpr int O_Q34 = O_Q12 + 1280;
constexpr int O_Y12 = O_Q34 + 2048 - 2176;
constexpr int O_Y34 = O_Y12 + 8704 - 4352;
constexpr int O_W3 = O_Y34 + 8704 + 256;
constexpr int O_W4 = O_W3 + 2048 + 256;
constexpr int O_W5 = O_W4 + 2048;
constexpr int O_U = HL_END;
constexpr int O_RAW = O_U + 6144;
constexpr int O_W1 = O_U + 6144 + 256;
constexpr int O_W2 = O_W1 + 3072 + 256;
constexpr int O_ST = O_RAW;
constexpr int O_KN = O_W2 + 3072;
constexpr int O_A12 = O_KN + 1344;
constexpr int O_A3 = O_A12 + 384;
constexpr int O_KQ = O_A3 + 304;
constexpr int WG_BYTES = 44032;
static_assert(O_W5 + 2048 <= HL_END && O_KQ + 16 <= WG_BYTES && WG_BYTES % 1024 == 0 && O_RAW + 8192 <= WG_BYTES, "map");

struct cplx { float r, i; };
__device__ __forceinline__ cplx cmul(cplx a, cplx b) {
    cplx o;
    o.r = fmaf(a.r, b.r, -a.i * b.i);
    o.i = fmaf(a.r, b.i, a.i * b.r);
    return o;
}
__device__ __forceinline__ cplx cexp_l(float lr, float li, float l) {
    const float e = exp2f((lr * l) * 1.4426950408889634f);
    const float ang = li * l;
    const float k = rintf(ang * 0.15915494309189535f);
    float r = fmaf(k, -6.2831854820251465f, ang);
    r = fmaf(k, 1.7484556000744487e-07f, r);
    cplx o;
    o.r = e * __cosf(r);
    o.i = e * __sinf(r);
    return o;
}
template <typename T> __device__ __forceinline__ T* sp(uint32_t a) {
    return reinterpret_cast<T*>(__cvta_shared_to_generic(a));
}
__device__ __forceinline__ void sts32(uint32_t a, uint32_t v) { *sp<uint32_t>(a) = v; }
__device__ __forceinline__ void sts16(uint32_t a, uint32_t v) { *sp<unsigned short>(a) = (unsigned short)v; }
__device__ __forceinline__ uint32_t lds16(uint32_t a) { return *sp<unsigned short>(a); }
__device__ __forceinline__ uint32_t lds32(uint32_t a) { return *sp<uint32_t>(a); }
__device__ __forceinline__ float ldsf(uint32_t a) { return *sp<float>(a); }
__device__ __forceinline__ uint2 lds64(uint32_t a) { return *sp<uint2>(a); }
__device__ __forceinline__ void sts64(uint32_t a, uint32_t x, uint32_t y) { *sp<uint2>(a) = make_uint2(x, y); }
__device__ __forceinline__ void sts64f(uint32_t a, float x, float y) { *sp<float2>(a) = make_float2(x, y); }
__device__ __forceinline__ void sts128(uint32_t a, uint32_t x, uint32_t y, uint32_t z, uint32_t w) {
    *sp<uint4>(a) = make_uint4(x, y, z, w);
}
__device__ __forceinline__ uint4 lds128(uint32_t a) { return *sp<uint4>(a); }
__device__ __forceinline__ void wg_bar(int id) { asm volatile("bar.sync %0, 128;" ::"r"(id) : "memory"); }
__device__ __forceinline__ uint32_t u_addr(uint32_t sb, int grp) {
    const int gq = grp + 128;
    return sb + O_U + (gq >> 3) * 128 + (((gq ^ (gq >> 3)) & 7) << 4);
}
template <int SCALE_D, int OA, int OB>
__device__ __forceinline__ void wgmma_ss_n32(float (&d)[16], uint32_t dl) {
    asm volatile(
        "{\n.reg .pred p;\n.reg .b32 lo;\n.reg .b64 x, y;\nsetp.ne.b32 p, %17, 0;\n"
        "add.u32 lo, %16, %18;\nmov.b64 x, {lo, 0x40000040};\nadd.u32 lo, %16, %19;\nmov.b64 y, {lo, 0x40000040};\n"
        "wgmma.mma_async.sync.aligned.m64n32k16.f32.bf16.bf16 "
        "{%0,%1,%2,%3,%4,%5,%6,%7,%8,%9,%10,%11,%12,%13,%14,%15}, x, y, p, 1, 1, 0, 0;\n}\n"
        : "+f"(d[0]), "+f"(d[1]), "+f"(d[2]), "+f"(d[3]), "+f"(d[4]), "+f"(d[5]), "+f"(d[6]), "+f"(d[7]),
          "+f"(d[8]), "+f"(d[9]), "+f"(d[10]), "+f"(d[11]), "+f"(d[12]), "+f"(d[13]), "+f"(d[14]), "+f"(d[15])
        : "r"(dl), "n"(SCALE_D), "n"(OA), "n"(OB));
}
template <int OB>
__device__ __forceinline__ void wgmma_rs_n32(float (&d)[16], uint32_t a0, uint32_t a1, uint32_t a2, uint32_t a3,
                                             uint32_t dl) {
    asm volatile(
        "{\n.reg .pred p;\n.reg .b32 lo;\n.reg .b64 y;\nsetp.ne.b32 p, 1, 0;\n"
        "add.u32 lo, %20, %21;\nmov.b64 y, {lo, 0x40000040};\n"
        "wgmma.mma_async.sync.aligned.m64n32k16.f32.bf16.bf16 "
        "{%0,%1,%2,%3,%4,%5,%6,%7,%8,%9,%10,%11,%12,%13,%14,%15}, {%16,%17,%18,%19}, y, p, 1, 1, 0;\n}\n"
        : "+f"(d[0]), "+f"(d[1]), "+f"(d[2]), "+f"(d[3]), "+f"(d[4]), "+f"(d[5]), "+f"(d[6]), "+f"(d[7]),
          "+f"(d[8]), "+f"(d[9]), "+f"(d[10]), "+f"(d[11]), "+f"(d[12]), "+f"(d[13]), "+f"(d[14]), "+f"(d[15])
        : "r"(a0), "r"(a1), "r"(a2), "r"(a3), "r"(dl), "n"(OB));
}
template <int KS> struct KgenSteps {
    static __device__ __forceinline__ void run(float (&d)[16], uint32_t dl) {
        KgenSteps<KS - 1>::run(d, dl);
        constexpr int k = KS - 1;
        wgmma_ss_n32<(k > 0), (O_H + (k / 4) * 3072 + (k % 4) * 32) / 16, (O_L + (k / 4) * 4096 + (k % 4) * 32) / 16>(d, dl);
    }
};
template <> struct KgenSteps<0> { static __device__ __forceinline__ void run(float (&)[16], uint32_t) {} };
template <int K0, int N, int I> struct NearSteps {
    static __device__ __forceinline__ void run(float (&d)[16], const uint4 (&f)[N], uint32_t dl) {
        NearSteps<K0, N, I - 1>::run(d, f, dl);
        constexpr int k = K0 + I - 1, dd = k / 4, kk = 4 * dd - (k - 3);
        wgmma_rs_n32<(O_U + (16 - dd) * 128 + kk * 32) / 16>(d, f[I - 1].x, f[I - 1].y, f[I - 1].z, f[I - 1].w, dl);
    }
};
template <int K0, int N> struct NearSteps<K0, N, 0> {
    static __device__ __forceinline__ void run(float (&)[16], const uint4 (&)[N], uint32_t) {}
};
template <int N>
__device__ __forceinline__ void load_toep(uint4 (&f)[N], uint32_t addr, uint32_t& prev) {
#pragma unroll
    for (int k = 0; k < N; k++)
    { const uint2 v = lds64(addr + k * 128); f[k].x = v.x; f[k].y = v.y; }
#pragma unroll
    for (int k = 0; k < N; k++) {
        f[k].z = prev;
        f[k].w = f[k].x;
        prev = f[k].y;
    }
}
__device__ __forceinline__ void mma16816(float (&d)[4], uint32_t a0, uint32_t a1, uint32_t a2, uint32_t b0,
                                         uint32_t b1) {
    asm("mma.sync.aligned.m16n8k16.row.col.f32.bf16.bf16.f32 {%0,%1,%2,%3}, {%4,%5,%6,%4}, {%7,%8}, {%0,%1,%2,%3};"
                 : "+f"(d[0]), "+f"(d[1]), "+f"(d[2]), "+f"(d[3])
                 : "r"(a0), "r"(a1), "r"(a2), "r"(b0), "r"(b1));
}
__device__ __forceinline__ uint4 ldsm_x4_t(uint32_t addr) {
    uint4 r;
    asm volatile("ldmatrix.sync.aligned.m8n8.x4.trans.shared.b16 {%0,%1,%2,%3}, [%4];"
                 : "=r"(r.x), "=r"(r.y), "=r"(r.z), "=r"(r.w) : "r"(addr));
    return r;
}
struct Params { const bf16 *A_re, *A_im, *B_re, *B_im, *C_re, *C_im, *log_dt, *Dskip; };
struct ModeIn { float ar, ai, br, bi, cr, ci, ldt, dsk; };
__device__ __forceinline__ ModeIn load_mode(const Params& p, int d, int n) {
    ModeIn m;
    const int i = d * N_MODES + n;
    m.ar = __bfloat162float(p.A_re[i]); m.ai = __bfloat162float(p.A_im[i]);
    m.br = __bfloat162float(p.B_re[i]); m.bi = __bfloat162float(p.B_im[i]);
    m.cr = __bfloat162float(p.C_re[i]); m.ci = __bfloat162float(p.C_im[i]);
    m.ldt = __bfloat162float(p.log_dt[d]); m.dsk = __bfloat162float(p.Dskip[d]);
    return m;
}

__device__ __forceinline__ void gen_powers(const ModeIn& mi, uint32_t sb, int t) {
    const float dt = bf16r(expf(mi.ldt));
    const float lr = dt * mi.ar, li = dt * mi.ai;
    const float br = dt * mi.br, bi = dt * mi.bi;
    cplx c;
    c.r = mi.cr * br - mi.ci * bi;
    c.i = mi.cr * bi + mi.ci * br;
    const cplx z = cexp_l(lr, li, 1.f), wv = cexp_l(lr, li, 8.f), Z = cexp_l(lr, li, 256.f);
    const cplx z2 = cmul(z, z), z4 = cmul(z2, z2);
    const uint32_t x0 = ((t & 31) >> 2) * 16 + (t & 3) * 4;
    uint32_t xs[8];
#pragma unroll
    for (int j = 0; j < 8; j++) xs[j] = sb + (x0 ^ (j << 4));
    const uint32_t ho = O_H + (t >> 5) * 3072, lo_ = O_L + (t >> 5) * 4096;
#define PUT_H(row, v) sts32(xs[(row) & 7] + ho + (row) * 128, pack_bf16((v).r, -(v).i))
#define PUT_L(row, v) sts32(xs[(row) & 7] + lo_ + (row) * 128, pack_bf16((v).r, (v).i))
    cplx h = c;
    PUT_H(0, h);
#pragma unroll
    for (int k = 1; k < 8; k++) { h = cmul(h, z); PUT_H(k, h); }
    cplx hz = cmul(c, Z);
    PUT_H(8, hz);
    { cplx a = cmul(hz, z2); PUT_H(9, a); a = cmul(hz, z4); PUT_H(10, a); a = cmul(a, z2); PUT_H(11, a); }
    hz = cmul(hz, Z); PUT_H(12, hz);
    { cplx a = cmul(hz, z4); PUT_H(13, a); }
    hz = cmul(hz, Z); PUT_H(14, hz);
    { cplx a = cmul(hz, z4); PUT_H(15, a); }
#pragma unroll
    for (int k = 16; k < 21; k++) { hz = cmul(hz, Z); PUT_H(k, hz); }
    const cplx w2 = cmul(wv, wv);
    cplx le, lo = wv;
    le.r = 1.f; le.i = 0.f;
    uint32_t lb = lo_;
#pragma unroll 1
    for (int kb = 0; kb < 4; kb++) {
#pragma unroll
        for (int k = 0; k < 8; k += 2) {
            sts32(xs[k] + lb + k * 128, pack_bf16(le.r, le.i));
            sts32(xs[k + 1] + lb + (k + 1) * 128, pack_bf16(lo.r, lo.i));
            le = cmul(le, w2); lo = cmul(lo, w2);
        }
        lb += 1024;
    }
}

__device__ __forceinline__ uint4 pack8(const float (&v)[8]) {
    return make_uint4(pack_bf16(v[0], v[1]), pack_bf16(v[2], v[3]), pack_bf16(v[4], v[5]), pack_bf16(v[6], v[7]));
}
__device__ __forceinline__ void st16B(uint32_t a, const uint4& v) { *sp<uint4>(a) = v; }

__device__ __forceinline__ void build_windows(uint32_t sb, int t) {
    if (t < 64) {
        const int which = t >> 4;
        sts128(sb + (which == 0 ? O_W1 : which == 1 ? O_W2 : which == 2 ? O_W3 : O_W4) - 256 + (t & 15) * 16, 0, 0, 0, 0);
    }
#pragma unroll
    for (int r = 0; r < 2; r++) {
        const int grp = t + r * 128;
        if (grp < 192) {
            const uint4 c0 = lds128(u_addr(sb, grp - 2)), c1 = lds128(u_addr(sb, grp - 1)), c2 = lds128(u_addr(sb, grp));
            float v[24];
            const uint32_t ww[12] = {c0.x, c0.y, c0.z, c0.w, c1.x, c1.y, c1.z, c1.w, c2.x, c2.y, c2.z, c2.w};
#pragma unroll
            for (int i = 2; i < 11; i++) { v[2 * i] = bf_lo(ww[i]); v[2 * i + 1] = bf_hi(ww[i]); }
            float p2[15];
#pragma unroll
            for (int j = 0; j < 15; j++) p2[j] = v[5 + j] + v[6 + j];
            float b1[8], b2[8];
#pragma unroll
            for (int i = 0; i < 8; i++) {
                b2[i] = p2[i + 6] + v[13 + i];
                b1[i] = p2[i + 1] + p2[i + 3] + v[10 + i];
            }
            st16B(sb + O_W1 + grp * 16, pack8(b1));
            st16B(sb + O_W2 + grp * 16, pack8(b2));
            if (r == 0) {
                float b3[8], b5[8];
#pragma unroll
                for (int i = 0; i < 8; i++) {
                    b3[i] = b1[i] + v[11 + i] + v[5 + i];
                    b5[i] = p2[i + 7];
                }
                st16B(sb + O_W3 + grp * 16, pack8(b3));
                st16B(sb + O_W5 + grp * 16, pack8(b5));
                st16B(sb + O_W4 + grp * 16, make_uint4(hadd2_bf(ww[6], ww[2]), hadd2_bf(ww[7], ww[3]),
                                                       hadd2_bf(ww[8], ww[4]), hadd2_bf(ww[9], ww[5])));
            }
        }
    }
}

__device__ __forceinline__ void build_tables(float (&kd)[16], float dskip, uint32_t sb, int t, int bar) {
    const int lane = t & 31, w = t >> 5, g = lane >> 2, tq = lane & 3;
    if (w == 0) {
        if (lane == 0) kd[0] += dskip;
        const uint32_t kn = sb + O_KN + 128;
#pragma unroll
        for (int j = 0; j < 4; j++) {
            const int lo = 8 * j + 2 * tq;
            const uint32_t p0 = pack_bf16(kd[4 * j], kd[4 * j + 1]), p1 = pack_bf16(kd[4 * j + 2], kd[4 * j + 3]);
            sts16(kn + (g + 8 * lo) * 2, p0);
            sts16(kn + (g + 8 * lo + 8) * 2, p0 >> 16);
            if (g < 4) {
#pragma unroll
                for (int e = 0; e < 2; e++) {
                    const uint32_t val = e ? (p1 >> 16) : p1, ad = kn + (256 + 2 * g + 8 * (lo + e)) * 2;
                    sts16(ad, val);
                    if (!(g & 1)) {
                        sts16(ad + 2, val);
                        if (g + lo + e > 0) sts16(ad - 2, val);
                    }
                }
            } else {
#pragma unroll
                for (int e = 0; e < 2; e++) {
                    const uint32_t val = e ? (p1 >> 16) : p1;
                    const int i8 = 64 + (g >= 6 ? 32 : 0) + lo + e;
                    if (j > 0 || i8 >= 66) {
                        sts16(sb + O_A12 + (i8 - 48) * 4 - ((g & 1) ? 0 : 2), val);
                    } else if (g & 1) {
                        sts16(kn + (8 * i8 + 3) * 2, val); sts16(kn + (8 * i8 + 4) * 2, val); sts16(kn + (8 * i8 + 5) * 2, val);
                    } else {
#pragma unroll
                        for (int dd = -2; dd <= 2; dd++)
                            if (i8 == 65 || dd >= -1) sts16(kn + (8 * i8 + dd) * 2, val);
                    }
                }
            }
        }
    } else if (w == 1) {
        if (g < 4) {
#pragma unroll
            for (int j = 0; j < 4; j++) {
                const int i8 = 128 + 32 * g + 8 * j + 2 * tq;
                const uint32_t p0 = pack_bf16(kd[4 * j], kd[4 * j + 1]);
                if (i8 == 128) { sts16(sb + O_A12 + (127 - 48) * 4 + 2, p0); sts16(sb + O_KQ, p0); }
                else sts16(sb + O_A3 + (i8 - 1 - 112) * 2, p0);
                sts16(sb + O_A3 + (i8 - 112) * 2, p0 >> 16);
            }
        } else if (lane == 16) {
            sts16(sb + O_A3 + (255 - 112) * 2, pack_bf16(kd[0], 0.f));
        }
    }
    wg_bar(bar);
    DBG1(4);
    {
#pragma unroll
        for (int r = 0; r < 2; r++) {
            const int i = t + r * 128;
            if (i < 160) {
                const uint32_t ka = sb + O_KN + (4 * i + 8) * 2;
                const uint32_t wm = lds32(ka - 4), w3 = lds32(ka + 12);
                const uint2 wa = lds64(ka), wb = lds64(ka + 16);
                const uint32_t w0 = wa.x, w1 = wa.y, w4 = wb.x, w5 = wb.y;
                sts128(sb + O_Q + i * 32, __byte_perm(w0, wm, 0x7610), __byte_perm(w4, w3, 0x7610),
                       __byte_perm(w0, w0, 0x1032), __byte_perm(w4, w4, 0x1032));
                sts128(sb + O_Q + i * 32 + 16, __byte_perm(w1, w0, 0x7610), __byte_perm(w5, w4, 0x7610),
                       __byte_perm(w1, w1, 0x1032), __byte_perm(w5, w5, 0x1032));
            }
        }
        {
            const uint32_t aa = sb + O_A3 + (8 + t) * 2;
            const uint32_t p0 = lds16(aa) | (lds16(aa - 2) << 16), p1 = lds16(aa + 16) | (lds16(aa + 14) << 16);
            const uint32_t msk = (t & 1) ? 0x0000ffffu : 0xffff0000u;
            sts128(sb + O_Q34 + t * 16, p0, p1, p0 & msk, p1 & msk);
        }
        if (t >= 48) {
            const uint32_t aa = sb + O_A12 + (t - 48 + 8) * 4;
            const uint32_t e0 = lds32(aa), e1 = lds32(aa - 4), f0 = lds32(aa + 32), f1 = lds32(aa + 28);
            sts128(sb + O_Q12 + (t - 48) * 16, __byte_perm(e0, e1, 0x7632), __byte_perm(f0, f1, 0x7632),
                   __byte_perm(e0, e1, 0x5410), __byte_perm(f0, f1, 0x5410));
        }
    }
}

__device__ __forceinline__ void convolve(int d, uint32_t sb, int t, int bar, const CUtensorMap* tmo) {
    const int lane = t & 31, w = t >> 5, g = lane >> 2, tq = lane & 3;
    const uint32_t dl = (sb & 0x3FFFF) >> 4;
    float y[16];
#pragma unroll
    for (int i = 0; i < 16; i++) y[i] = 0.f;
    {
        const uint32_t qa = sb + O_Q + (16 * w + g - 2 * tq + 56 - 48) * 8;
        uint32_t prev = 0;
        uint32_t qp = qa, du = dl;
#pragma unroll 1
        for (int jj = 0; jj < 4; jj++) {
            uint4 F[8];
            load_toep<8>(F, qp, prev);
            WG_FENCE();
            NearSteps<0, 8, 8>::run(y, F, du);
            WG_COMMIT();
            WG_WAIT(0);
            qp += 8 * 128;
            du -= 16;
        }
        uint4 FC[5];
        load_toep<5>(FC, qp, prev);
        WG_FENCE();
        NearSteps<0, 5, 5>::run(y, FC, du);
        WG_COMMIT();
        WG_WAIT(0);
#pragma unroll
        for (int i = 0; i < 16; i++) asm volatile("" : "+f"(y[i])::"memory");
    }
    DBG1(6);
    {
        const int par = w & 1;
        const uint32_t qoff = sb + (g - 2 * tq) * 16;
        const uint32_t roff = sb + (lane & 15) * 16 + par * 256;
        const uint32_t yoff = sb + (136 * par + 8 * g + 2 * tq) * 4;
        if (w < 2) {
            const uint32_t wb = roff + ((lane >> 4) ? O_W2 : O_W1);
            uint4 f[5];
#pragma unroll
            for (int q = 4; q <= 8; q++) f[q - 4] = lds128(qoff + O_Q12 + (16 * q - 56) * 16);
            uint4 bt[12];
#pragma unroll
            for (int i = 0; i < 6; i++) {
                if (i == 0) bt[0] = ldsm_x4_t(wb - 256);
                bt[2 * i + 1] = ldsm_x4_t(wb + (2 * i) * 256);
                if (i > 0) bt[2 * i] = ldsm_x4_t(wb + (2 * i - 1) * 256);
                float a0[4] = {0.f, 0.f, 0.f, 0.f}, a1[4] = {0.f, 0.f, 0.f, 0.f};
#pragma unroll
                for (int q = 4; q <= 8; q++) {
                    const int k = 2 * i + 4 - q;
                    if (k >= -1) {
                        mma16816(a0, f[q - 4].x, f[q - 4].y, q > 4 ? f[q > 4 ? q - 5 : 0].y : 0u, bt[k + 1].x, bt[k + 1].y);
                        mma16816(a1, f[q - 4].z, f[q - 4].w, q > 4 ? f[q > 4 ? q - 5 : 0].w : 0u, bt[k + 1].z, bt[k + 1].w);
                    }
                }
                const uint32_t ya = yoff + O_Y12 + 136 * (4 + 2 * i) * 4;
                sts64f(ya, a0[0] + a1[0], a0[1] + a1[1]);
                sts64f(ya + 256, a0[2] + a1[2], a0[3] + a1[3]);
            }
        } else {
            const uint32_t wb = roff + ((lane >> 4) ? O_W4 : O_W3);
            uint4 bt[8];
#pragma unroll
            for (int k = 0; k < 8; k++) bt[k] = ldsm_x4_t(wb + (k - 1) * 256);
            const uint4 b5a = ldsm_x4_t(roff + O_W5 + (lane >> 4) * 512), b5b = ldsm_x4_t(roff + O_W5 + 1024 + (lane >> 4) * 512);
            const uint32_t kq = lds16(sb + O_KQ);
            const uint32_t dg = (g == 2 * tq) ? kq : ((g == 2 * tq + 1) ? (kq << 16) : 0u);
            float acc[4][4];
#pragma unroll
            for (int i = 0; i < 4; i++)
#pragma unroll
                for (int j = 0; j < 4; j++) acc[i][j] = 0.f;
            mma16816(acc[0], dg, 0u, 0u, b5a.x, b5a.y);
            mma16816(acc[1], dg, 0u, 0u, b5a.z, b5a.w);
            mma16816(acc[2], dg, 0u, 0u, b5b.x, b5b.y);
            mma16816(acc[3], dg, 0u, 0u, b5b.z, b5b.w);
            uint32_t pa = 0, pb = 0;
#pragma unroll
            for (int q = 8; q <= 15; q++) {
                const uint4 f = lds128(qoff + O_Q34 + (16 * q - 120) * 16);
#pragma unroll
                for (int i = 0; i < 4; i++) {
                    const int k = 2 * i + 8 - q;
                    if (k >= -1) mma16816(acc[i], f.x, f.y, pa, bt[k + 1].x, bt[k + 1].y);
                }
#pragma unroll
                for (int i = 0; i < 4; i++) {
                    const int k = 2 * i + 8 - q;
                    if (k >= -1) mma16816(acc[i], f.z, f.w, pb, bt[k + 1].z, bt[k + 1].w);
                }
                pa = f.y; pb = f.w;
            }
#pragma unroll
            for (int i = 0; i < 4; i++) {
                const uint32_t ya = yoff + O_Y34 + 136 * (8 + 2 * i) * 4;
                sts64f(ya, acc[i][0], acc[i][1]);
                sts64f(ya + 256, acc[i][2], acc[i][3]);
            }
        }
    }
    wg_bar(bar);
    DBG1(7);
    {
        const uint32_t yb = sb + (136 * tq + 16 * w + g) * 4;
#pragma unroll
        for (int j = 1; j < 4; j++)
#pragma unroll
            for (int e = 0; e < 4; e++) {
                const uint32_t o = yb + (544 * j + 64 * (e & 1) + 8 * (e >> 1)) * 4;
                y[4 * j + e] += ldsf(o + O_Y12);
                if (j >= 2) y[4 * j + e] += ldsf(o + O_Y34);
            }
#pragma unroll
        for (int jp = 0; jp < 2; jp++) {
            const int a = 8 * (2 * jp + (lane >> 4)) + (lane & 7);
            const uint32_t addr = sb + O_ST + a * 128 + (((2 * w + ((lane >> 3) & 1)) ^ (lane & 7)) << 4);
            asm volatile("stmatrix.sync.aligned.m8n8.x4.trans.shared.b16 [%0], {%1,%2,%3,%4};" ::"r"(addr),
                         "r"(pack_bf16(y[8 * jp + 0], y[8 * jp + 1])), "r"(pack_bf16(y[8 * jp + 2], y[8 * jp + 3])),
                         "r"(pack_bf16(y[8 * jp + 4], y[8 * jp + 5])), "r"(pack_bf16(y[8 * jp + 6], y[8 * jp + 7]))
                         : "memory");
        }
        asm volatile("fence.proxy.async.shared::cta;" ::: "memory");
        wg_bar(bar);
        if (t == 0) {
            asm volatile("cp.async.bulk.tensor.2d.global.shared::cta.bulk_group [%0, {%1, %2}], [%3];"
                         ::"l"(tmo), "r"(0), "r"(d * 32), "r"(sb + O_ST) : "memory");
            asm volatile("cp.async.bulk.commit_group;" ::: "memory");
            asm volatile("cp.async.bulk.wait_group.read 0;" ::: "memory");
        }
        DBG1(8);
    }
}

constexpr int K1_WGS = 5;
constexpr int O_XTRA = K1_WGS * WG_BYTES;
constexpr int K1_SMEM = O_XTRA + 3 * 4096;
constexpr int K1_CTAS = (D_MODEL + K1_WGS - 1) / K1_WGS;
constexpr int K1_STAT = 16;
__device__ __forceinline__ uint32_t raw_box(uint32_t sbase, int i) {
    return i < K1_WGS ? sbase + i * WG_BYTES + O_RAW : sbase + O_XTRA + (i - K1_WGS) * 4096;
}
__device__ __forceinline__ void transpose_window(uint32_t sbase, int warp, int lane, int ch0) {
    const int ch = (lane >> 2) + ch0;
    const uint32_t ub = sbase + ch * WG_BYTES + (lane & 3) * 4;
#pragma unroll
    for (int k = 0; k < 4; k++) {
        const int gi = warp + k * (4 * K1_WGS);
        if (gi < 64) {
            const uint4 v = ldsm_x4_t(raw_box(sbase, gi >> 3) + (gi & 7) * 512 + lane * 16);
            if (ch >= 0 && ch < K1_WGS) {
                const uint32_t a0 = u_addr(ub, 4 * gi);
                sts32(a0, v.x);
                sts32(a0 ^ 16, v.y);
                sts32(a0 ^ 32, v.z);
                sts32(a0 ^ 48, v.w);
            }
        }
    }
}

__global__ void __launch_bounds__(128 * K1_WGS, 1)
ssm_kernel(const __grid_constant__ CUtensorMap tmc, const __grid_constant__ CUtensorMap tmo,
           const bf16* __restrict__ x, const bf16* __restrict__ gw, Params p) {
    extern __shared__ __align__(1024) uint8_t smem_raw[];
    const uint32_t sbase = smem_u32(smem_raw);
    const int tid = threadIdx.x, t = tid & 127, lane = tid & 31;
    const int wg = __shfl_sync(0xffffffffu, tid >> 7, 0), warp = __shfl_sync(0xffffffffu, tid >> 5, 0);
    const int d0 = blockIdx.x * K1_WGS, d = min(d0 + wg, D_MODEL - 1);
    const uint32_t sb = sbase + wg * WG_BYTES;
    const uint32_t xbar = sbase + WG_BYTES - 16;
    const int dw = d0 & ~7;
    const bool two = (d0 & 7) > 3 && dw + 8 < D_MODEL;
    DBG1(0);
    if (blockIdx.x == 0) {
        if (tid == 0) {
            g_epoch = g_epoch + 1;
            asm volatile("fence.acq_rel.gpu;" ::: "memory");
        }
        __syncthreads();
    }
    asm volatile("griddepcontrol.launch_dependents;");
    if (blockIdx.x >= K1_CTAS) {
        const uint32_t tag = (g_stat_epoch[blockIdx.x - K1_CTAS] + 1) & 1u;
        __syncthreads();
        if (tid == 0) g_stat_epoch[blockIdx.x - K1_CTAS] = g_stat_epoch[blockIdx.x - K1_CTAS] + 1;
        uint32_t gr[9];
#pragma unroll
        for (int i = 0; i < 9; i++) gr[i] = __ldg(reinterpret_cast<const uint32_t*>(gw) + lane + 32 * i);
#pragma unroll 1
        for (int row = (blockIdx.x - K1_CTAS) * (4 * K1_WGS) + warp; row < L_SEQ; row += 2 * K1_STAT * 4 * K1_WGS) {
            const int row2 = min(row + K1_STAT * 4 * K1_WGS, L_SEQ - 1);
            uint32_t xr[2][9];
#pragma unroll
            for (int i = 0; i < 9; i++) {
                xr[0][i] = __ldg(reinterpret_cast<const uint32_t*>(x + (size_t)row * D_MODEL) + lane + 32 * i);
                xr[1][i] = __ldg(reinterpret_cast<const uint32_t*>(x + (size_t)row2 * D_MODEL) + lane + 32 * i);
            }
#pragma unroll
            for (int h = 0; h < 2; h++) {
                float s = 0.f, gs = 0.f;
#pragma unroll
                for (int i = 0; i < 9; i++) {
                    s += bf_lo(xr[h][i]) + bf_hi(xr[h][i]);
                    const uint32_t pr = hmul2_bf(xr[h][i], gr[i]);
                    gs += bf_lo(pr) + bf_hi(pr);
                }
#pragma unroll
                for (int o = 16; o; o >>= 1) {
                    s += __shfl_xor_sync(~0u, s, o);
                    gs += __shfl_xor_sync(~0u, gs, o);
                }
                const float mean = s * (1.f / D_MODEL);
                float q = 0.f;
#pragma unroll
                for (int i = 0; i < 9; i++) {
                    const float a = bf_lo(xr[h][i]) - mean, b = bf_hi(xr[h][i]) - mean;
                    q = fmaf(a, a, fmaf(b, b, q));
                }
#pragma unroll
                for (int o = 16; o; o >>= 1) q += __shfl_xor_sync(~0u, q, o);
                if (lane == 0) {
                    const float var = bf16r(q * (1.f / D_MODEL));
                    const float den = bf16r(sqrtf(bf16r(var + 1e-5f)));
                    const int r = h ? row2 : row;
                    const unsigned long long e = ((unsigned long long)((__float_as_uint(__fdividef(1.f, den)) & ~1u) | tag) << 32) |
                                                 pack_bf16(mean, mean);
                    asm volatile("st.relaxed.gpu.global.b64 [%0], %1;" ::"l"(&g_rowstat[r]), "l"(e) : "memory");
                    g_gate[r] = bf16r(__fdividef(1.f, 1.f + __expf(-bf16r(gs))));
                }
            }
        }
        return;
    }
    if (tid == 0) {
        mbar_init(xbar, 1);
        asm volatile("fence.mbarrier_init.release.cluster;" ::: "memory");
        mbar_expect(xbar, 8 * 4096);
#pragma unroll
        for (int i = 0; i < 8; i++) tma2d(raw_box(sbase, i), &tmc, dw, i * 256, xbar);
    }
    const ModeIn mi = load_mode(p, d, t);
    sts128(sb + O_U + t * 16, 0, 0, 0, 0);
    sts128(sb + O_KN + t * 16, 0, 0, 0, 0);
    gen_powers(mi, sb, t);
    DBG1(1);
    asm volatile("fence.proxy.async.shared::cta;" ::: "memory");
    __syncthreads();
    float kd[16];
    WG_FENCE();
    KgenSteps<16>::run(kd, (sb & 0x3FFFF) >> 4);
    WG_COMMIT();
    mbar_wait(xbar, 0);
    DBG1(2);
    transpose_window(sbase, warp, lane, dw - d0);
    if (two) {
        asm volatile("fence.proxy.async.shared::cta;" ::: "memory");
        __syncthreads();
        if (tid == 0) {
            mbar_expect(xbar, 8 * 4096);
#pragma unroll
            for (int i = 0; i < 8; i++) tma2d(raw_box(sbase, i), &tmc, dw + 8, i * 256, xbar);
        }
    }
    DBG1(3);
    WG_WAIT(0);
#pragma unroll
    for (int i = 0; i < 16; i++) asm volatile("" : "+f"(kd[i])::"memory");
    build_tables(kd, mi.dsk, sb, t, 1 + wg);
    if (two) {
        mbar_wait(xbar, 1);
        transpose_window(sbase, warp, lane, dw + 8 - d0);
    }
    asm volatile("fence.proxy.async.shared::cta;" ::: "memory");
    __syncthreads();
    DBG1(5);
    build_windows(sb, t);
    wg_bar(1 + wg);
    DBG1(9);
    if (d0 + wg < D_MODEL) convolve(d, sb, t, 1 + wg, &tmo);
}
}

constexpr int XT_BYTES = 128 * D_MODEL * 2;
constexpr int STAGE_BYTES = 96 * 128;
constexpr int NSTAGE = 6;
constexpr int SM_STAGES = XT_BYTES;
constexpr int SM_BARS = SM_STAGES + NSTAGE * STAGE_BYTES;
constexpr int SM_B1 = SM_BARS + 512;
constexpr int SM_B2 = SM_B1 + 576 * 4;
constexpr int MLP_SMEM = SM_B2 + 576 * 2;
__host__ __device__ constexpr int red_buf(int c) { return c < 7 ? c * 18432 : SM_STAGES + (c - 7) * 18432; }
constexpr int BAR_FULL = 0, BAR_EMPTY = 48, BAR_X = 96, BAR_PARKFREE = 168, BAR_STORED = 176, BAR_LOADED = 248, BAR_A = 320;

__device__ __forceinline__ float gelu2(float x) {
    const float k0 = 0.7978845608028654f, k1 = 0.7978845608028654f * 0.044715f;
    float u = x * fmaf(x * x, k1, k0);
    float th;
    asm("tanh.approx.f32 %0, %1;" : "=f"(th) : "f"(u));
    return fmaf(x, th, x);
}

__device__ __forceinline__ void epi_gelu(const float (&acc)[32], int i, uint32_t b1_addr, float r0, float r1,
                                         uint32_t (&o)[4]) {
    float b0, b1, b2, b3;
    asm volatile("ld.shared.v4.f32 {%0,%1,%2,%3}, [%4];"
                 : "=f"(b0), "=f"(b1), "=f"(b2), "=f"(b3) : "r"(b1_addr + i * 16));
    o[0] = pack_bf16(gelu2(fmaf(acc[8 * i + 0], r0, b0)), gelu2(fmaf(acc[8 * i + 1], r0, b1)));
    o[1] = pack_bf16(gelu2(fmaf(acc[8 * i + 2], r1, b0)), gelu2(fmaf(acc[8 * i + 3], r1, b1)));
    o[2] = pack_bf16(gelu2(fmaf(acc[8 * i + 4], r0, b2)), gelu2(fmaf(acc[8 * i + 5], r0, b3)));
    o[3] = pack_bf16(gelu2(fmaf(acc[8 * i + 6], r1, b2)), gelu2(fmaf(acc[8 * i + 7], r1, b3)));
}
__device__ __forceinline__ void epi_park(const float (&acc)[32], int i, uint32_t b1_addr, uint32_t park_addr,
                                         float r0, float r1) {
    uint32_t o[4];
    epi_gelu(acc, i, b1_addr, r0, r1, o);
    asm volatile("st.shared.v4.b32 [%0], {%1,%2,%3,%4};" ::"r"(park_addr + i * 4096), "r"(o[0]), "r"(o[1]),
                 "r"(o[2]), "r"(o[3]) : "memory");
}
__device__ __forceinline__ void epi_part(const float (&acc)[32], int i, uint4* part, uint32_t par) {
    uint4 v;
    v.x = (pack_bf16(acc[8 * i + 0], acc[8 * i + 1]) & ~1u) | par;
    v.y = pack_bf16(acc[8 * i + 2], acc[8 * i + 3]);
    v.z = (pack_bf16(acc[8 * i + 4], acc[8 * i + 5]) & ~1u) | par;
    v.w = pack_bf16(acc[8 * i + 6], acc[8 * i + 7]);
    asm volatile("{\n.reg .b128 q;\nmov.b128 q, {%1, %2};\nst.relaxed.gpu.global.b128 [%0], q;\n}\n" ::"l"(part + i * 32),
                 "l"(((unsigned long long)v.y << 32) | v.x), "l"(((unsigned long long)v.w << 32) | v.z) : "memory");
}
__device__ __forceinline__ void warp_arrive(uint32_t bar, int lane) {
    __syncwarp();
    if (lane == 0) asm volatile("mbarrier.arrive.shared::cta.b64 _, [%0];" ::"r"(bar) : "memory");
}

__device__ __forceinline__ void probe_partials(const uint4* unit, uint32_t par) {
    asm volatile(
        "{\n.reg .pred p;\n.reg .u32 n, v;\nmov.u32 n, 0;\n"
        "PROBE_LOOP:\n"
        "ld.relaxed.gpu.global.u32 v, [%0];\n"
        "xor.b32 v, v, %1;\n"
        "and.b32 v, v, 1;\n"
        "setp.ne.u32 p, v, 0;\n"
        "vote.sync.any.pred p, p, 0xffffffff;\n"
        "@!p bra PROBE_DONE;\n"
        "add.u32 n, n, 1;\n"
        "setp.lt.u32 p, n, 1048576;\n"
        "@p bra PROBE_LOOP;\n"
        "trap;\n"
        "PROBE_DONE:\n}\n" ::"l"(unit), "r"(par) : "memory");
}

__device__ __forceinline__ void finish_tile(int c, int tile, uint32_t sbase, uint32_t par, uint32_t gA, uint32_t gB,
                                            bf16* __restrict__ out) {
    const int lane = threadIdx.x & 31;
    const uint32_t buf = sbase + red_buf(c);
    const uint32_t a0 = buf + (tile >> 1) * 512 + lane * 16 + (tile & 1) * 8;
    uint2 v[8];
#pragma unroll
    for (int q = 0; q < 8; q++) v[q] = ssm::lds64(a0 + q * 2048);
    uint32_t ax, ay;
    asm volatile("ldmatrix.sync.aligned.m8n8.x2.trans.shared.b16 {%0,%1}, [%2];" : "=r"(ax), "=r"(ay)
                 : "r"(buf + 16384 + (lane & 7) * 32 + ((lane >> 3) & 1) * 16 + tile * 256) : "memory");
    const uint32_t bb = ssm::lds32(sbase + SM_B2 + c * 128 + (tile >> 1) * 32 + (lane & 3) * 8 + (tile & 1) * 4);
    const int m = blockIdx.x & 15, f = blockIdx.x >> 4;
    int tries = 0;
    while (true) {
        uint32_t bad = 0;
#pragma unroll
        for (int q = 0; q < 8; q++) bad |= v[q].x ^ par;
        if (!__any_sync(0xffffffffu, bad & 1)) break;
        const uint2* ps = reinterpret_cast<const uint2*>(
            g_part + ((m * 9 + c) * 8 + f) * (8 * 4 * 32) + (tile >> 1) * 32 + lane) + (tile & 1);
#pragma unroll
        for (int q = 0; q < 8; q++) {
            unsigned long long w;
            asm volatile("ld.relaxed.gpu.global.b64 %0, [%1];" : "=l"(w) : "l"(ps + q * 256) : "memory");
            v[q] = make_uint2((uint32_t)w, (uint32_t)(w >> 32));
        }
        if (++tries > (1 << 20)) asm volatile("trap;");
    }
    float sx0 = 0.f, sx1 = 0.f, sy0 = 0.f, sy1 = 0.f;
#pragma unroll
    for (int q = 0; q < 8; q++) {
        sx0 += bf_lo(v[q].x); sx1 += bf_hi(v[q].x);
        sy0 += bf_lo(v[q].y); sy1 += bf_hi(v[q].y);
    }
    const uint32_t half2 = 0x3f003f00u, one2 = 0x3f803f80u;
    uint32_t* o32 = reinterpret_cast<uint32_t*>(out + (m * 128 + f * 16 + (lane >> 2)) * D_MODEL + c * 64 + tile * 8 + 2 * (lane & 3));
    o32[0] = hadd2_bf(hmul2_bf(gA, ax), hmul2_bf(hsub2_bf(one2, gA), hfma2_bf(pack_bf16(sx0, sx1), half2, bb)));
    o32[4 * D_MODEL] = hadd2_bf(hmul2_bf(gB, ay), hmul2_bf(hsub2_bf(one2, gB), hfma2_bf(pack_bf16(sy0, sy1), half2, bb)));
}
constexpr int NFIN_HELP = 5;

template <int EPI>
__device__ __forceinline__ void run_chunk(float (&cur)[32], float (&prev)[32], const uint32_t (&af)[NAF][4],
                                          int parity, uint32_t bars, uint32_t desc0, uint32_t adesc0, uint32_t p0, uint32_t p1,
                                          uint4* part, bool sig, uint32_t rbar, int lane, float r0, float r1) {
#pragma unroll
    for (int s = 0; s < 6; s++) {
        mbar_wait(bars + BAR_FULL + s * 8, parity);
        WG_FENCE();
        mma_stage_rt(s, cur, af, desc0, adesc0);
        WG_COMMIT();
        if (s >= 1 && s <= 4) {
            if (EPI == 1) epi_park(prev, s - 1, p0, p1, r0, r1);
            if (EPI == 2) epi_part(prev, s - 1, part, p1);
        }
        if (s == 4 && EPI == 2) warp_arrive(p0, lane);
        WG_WAIT(1);
        if (sig) asm volatile("mbarrier.arrive.shared::cluster.b64 _, [%0];" ::"r"(rbar + ((s + 5) % 6) * 8) : "memory");
        if (s == 0) fence_acc(prev);
    }
}

__global__ void __cluster_dims__(2, 1, 1) __launch_bounds__(384, 1)
mlp_kernel(const __grid_constant__ CUtensorMap tmx, const __grid_constant__ CUtensorMap tmw1,
           const __grid_constant__ CUtensorMap tmw2, const __grid_constant__ CUtensorMap tma,
           const bf16* __restrict__ b1, const bf16* __restrict__ b2,
           bf16* __restrict__ out) {
    extern __shared__ __align__(1024) uint8_t smem_raw[];
    const uint32_t sbase = smem_u32(smem_raw);
    uint8_t* sgen = smem_raw;
    const int tid = threadIdx.x, lane = tid & 31;
    const int warp = __shfl_sync(0xffffffffu, tid >> 5, 0);
    const int wgid = __shfl_sync(0xffffffffu, tid >> 7, 0);
    const int m = blockIdx.x & 15, f = blockIdx.x >> 4;
    const uint32_t rank = m & 1;
    const uint32_t bars = sbase + SM_BARS;
    if (warp == 0) DBG(12);

    if (tid == 0) {
        if (sbase & 1023) asm volatile("trap;");
        for (int i = 0; i < NSTAGE; i++) {
            mbar_init(bars + BAR_FULL + i * 8, 1);
            mbar_init(bars + BAR_EMPTY + i * 8, 4);
        }
        for (int i = 0; i < 9; i++) mbar_init(bars + BAR_X + i * 8, 1);
        mbar_init(bars + BAR_PARKFREE, 8);
        mbar_init(bars + BAR_A, 1);
        for (int i = 0; i < 9; i++) {
            mbar_init(bars + BAR_STORED + i * 8, 8);
            mbar_init(bars + BAR_LOADED + i * 8, 1);
        }
        asm volatile("fence.mbarrier_init.release.cluster;" ::: "memory");
        for (int j = 0; j < 3; j++) {
            mbar_expect(bars + BAR_X + j * 8, 16384);
            tma2d(sbase + j * 16384, &tmx, j * 64, m * 128, bars + BAR_X + j * 8);
        }
    }
    uint32_t b1v0 = 0, b1v1 = 0;
    if (wgid < 2) {
        const uint32_t* b1w = reinterpret_cast<const uint32_t*>(b1 + f * 576);
        b1v0 = __ldg(b1w + (tid >> 5) * 32 + (tid & 7) * 4 + ((tid >> 3) & 3));
        if (tid < 32) b1v1 = __ldg(b1w + 8 * 32 + (tid & 7) * 4 + ((tid >> 3) & 3));
    }
    __syncthreads();
    asm volatile("barrier.cluster.arrive.relaxed.aligned;\nbarrier.cluster.wait.aligned;" ::: "memory");

    if (warp == 0) DBG(0);
    if (wgid == 2) {
        asm volatile("setmaxnreg.dec.sync.aligned.u32 40;");
        if (warp == 8) {
            if (lane == 0) {
                const uint32_t dst0 = sbase + SM_STAGES + rank * (STAGE_BYTES / 2);
#pragma unroll 1
                for (int cc = 0; cc < 18; cc++) {
                    const CUtensorMap* tm = cc < 9 ? &tmw1 : &tmw2;
                    const int c0 = cc < 9 ? f * 576 + cc * 64 : (cc - 9) * 64;
                    const int c1 = (cc < 9 ? 0 : f * 576) + rank * 48;
                    const int par = (cc & 1) ^ 1;
#pragma unroll
                    for (int s = 0; s < 6; s++) {
                        mbar_wait(bars + BAR_EMPTY + s * 8, par);
                        mbar_expect(bars + BAR_FULL + s * 8, STAGE_BYTES);
                        tma2d_mc(dst0 + s * STAGE_BYTES, tm, c0, c1 + s * 96, bars + BAR_FULL + s * 8, 3);
                        if (cc == 0 && s >= 1 && s <= 3) {
#pragma unroll
                            for (int j = 2 * s + 1; j < 2 * s + 3; j++) {
                                mbar_expect(bars + BAR_X + j * 8, 16384);
                                tma2d(sbase + j * 16384, &tmx, j * 64, m * 128, bars + BAR_X + j * 8);
                            }
                        }
                    }
                }
            }
        } else if (warp == 9) {
            {
                uint32_t* b2s = reinterpret_cast<uint32_t*>(sgen + SM_B2);
                for (int w = lane; w < 288; w += 32) {
                    const int jj = w & 1, q = (w >> 1) & 3, ci = w >> 3;
                    b2s[w] = __ldg(reinterpret_cast<const uint32_t*>(b2) + ci * 8 + jj * 4 + q);
                }
                __syncwarp();
            }
            asm volatile("griddepcontrol.wait;" ::: "memory");
            const uint32_t par = __ldcg(&g_epoch);
            mbar_wait(bars + BAR_PARKFREE, 0);
            asm volatile("fence.proxy.async.shared::cta;" ::: "memory");
            const uint4* psrc = g_part + (m * 9 * 8 + f) * (8 * 4 * 32);
#pragma unroll 1
            for (int c = 0; c < 8; c++) {
                const uint32_t buf = sbase + red_buf(c);
                if (c == 7) {
                    mbar_wait(bars + BAR_EMPTY + 0, 1);
                    mbar_wait(bars + BAR_EMPTY + 8, 1);
                    mbar_wait(bars + BAR_EMPTY + 16, 1);
                }
                if (lane == 0) {
                    mbar_expect(bars + BAR_LOADED + c * 8, c < 8 ? 16384 + 2048 : 2048);
                    tma2d(buf + 16384, &tma, m * 128 + f * 16, c * 64, bars + BAR_LOADED + c * 8);
                    if (c == 7) {
                        mbar_expect(bars + BAR_LOADED + 64, 2048);
                        tma2d(sbase + red_buf(8) + 16384, &tma, m * 128 + f * 16, 8 * 64, bars + BAR_LOADED + 64);
                    }
                }
                mbar_wait(bars + BAR_STORED + c * 8, 0);
                probe_partials(psrc + (lane & 7) * 128 + 96 + 31, par);
                DBG(16 + c);
                if (lane == 0)
                    asm volatile("cp.async.bulk.shared::cluster.global.mbarrier::complete_tx::bytes [%0], [%1], 16384, [%2];"
                                 ::"r"(buf), "l"(psrc), "r"(bars + BAR_LOADED + c * 8) : "memory");
                psrc += 8 * 8 * 4 * 32;
            }
        }
        if (warp >= 10) {
            mbar_wait(bars + BAR_PARKFREE, 0);
            asm volatile("griddepcontrol.wait;" ::: "memory");
            const int t0 = m * 128 + f * 16 + (lane >> 2);
            const float g0 = __ldcg(&g_gate[t0]), g1 = __ldcg(&g_gate[t0 + 8]);
            const uint32_t par = __ldcg(&g_epoch) & 1u;
            const uint32_t gA = pack_bf16(g0, g0), gB = pack_bf16(g1, g1);
#pragma unroll 1
            for (int it = 0; it < NFIN_HELP * 4; it++) {
                if (!(it & 3)) mbar_wait(bars + BAR_LOADED + (it >> 2) * 8, 0);
                finish_tile(it >> 2, (it & 3) * 2 + (warp & 1), sbase, par, gA, gB, out);
            }
        }
        __syncwarp();
        asm volatile("barrier.cluster.arrive.relaxed.aligned;\nbarrier.cluster.wait.aligned;" ::: "memory");
    } else {
        asm volatile("setmaxnreg.inc.sync.aligned.u32 232;");
        const uint32_t par = __ldcg(&g_epoch) & 1u;
        uint2 rs0, rs1;
        {
            const uint2* rp = &g_rowstat[m * 128 + warp * 16 + (lane >> 2)];
            int tries = 0;
            while (true) {
                unsigned long long e0, e1;
                asm volatile("ld.relaxed.gpu.global.b64 %0, [%1];" : "=l"(e0) : "l"(rp) : "memory");
                asm volatile("ld.relaxed.gpu.global.b64 %0, [%1];" : "=l"(e1) : "l"(rp + 8) : "memory");
                rs0 = make_uint2((uint32_t)e0, (uint32_t)(e0 >> 32));
                rs1 = make_uint2((uint32_t)e1, (uint32_t)(e1 >> 32));
                if (!__any_sync(0xffffffffu, ((rs0.y ^ par) | (rs1.y ^ par)) & 1)) break;
                if (++tries > (1 << 22)) asm volatile("trap;");
            }
        }
        const int g = lane >> 2, tq = lane & 3;
        uint32_t af[NAF][4];
        float acc0[32], acc1[32];
        const bool sig = (tid & 127) < 2;
        uint32_t rbar;
        asm volatile("mapa.shared::cluster.u32 %0, %1, %2;" : "=r"(rbar) : "r"(bars + BAR_EMPTY), "r"(tid & 1));
        const uint32_t desc0 = ((sbase + SM_STAGES) & 0x3FFFF) >> 4;
        const uint32_t adesc0 = ((sbase + 8 * 16384 + wgid * 8192) & 0x3FFFF) >> 4;

        {
            float2* b1s = reinterpret_cast<float2*>(sgen + SM_B1);
            b1s[tid] = make_float2(bf_lo(b1v0), bf_hi(b1v0));
            if (tid < 32) b1s[256 + tid] = make_float2(bf_lo(b1v1), bf_hi(b1v1));
        }
        const float rstd0 = __uint_as_float(rs0.y), rstd1 = __uint_as_float(rs1.y);
        {
            const int lrow = warp * 16 + (lane & 7) + ((lane >> 3) & 1) * 8;
            const uint32_t rbase = sbase + lrow * 128;
            const int hi = lane >> 4, sw = lrow & 7;
#pragma unroll
            for (int s = 0; s < 6; s++) {
#pragma unroll
                for (int k = s * 6; k < s * 6 + 6; k++) {
                    const int j = k >> 2, kk = k & 3;
                    if (kk == 0 || k == s * 6) mbar_wait(bars + BAR_X + j * 8, 0);
                    uint32_t tmp[4];
                    uint32_t (&a)[4] = (k < NAF) ? af[(k < NAF) ? k : 0] : tmp;
                    const uint32_t addr = rbase + j * 16384 + (((kk * 2 + hi) ^ sw) << 4);
                    ldsm_x4(a, addr);
                    a[0] = hsub2_bf(a[0], rs0.x);
                    a[1] = hsub2_bf(a[1], rs1.x);
                    a[2] = hsub2_bf(a[2], rs0.x);
                    a[3] = hsub2_bf(a[3], rs1.x);
                    if (k >= NAF) stsm_x4(a, addr);
                }
                if (s == 5) {
                    asm volatile("fence.proxy.async.shared::cta;" ::: "memory");
                    asm volatile("bar.sync %0, 128;" ::"r"(3 + wgid) : "memory");
                    if (warp == 0) DBG(1);
                }
                mbar_wait(bars + BAR_FULL + s * 8, 0);
                WG_FENCE();
                mma_stage_rt(s, acc0, af, desc0, adesc0);
                WG_COMMIT();
                if (s > 0) {
                    WG_WAIT(1);
                    if (sig) asm volatile("mbarrier.arrive.shared::cluster.b64 _, [%0];" ::"r"(rbar + (s - 1) * 8) : "memory");
                }
            }
            asm volatile("bar.sync 1, 256;" ::: "memory");
        }
        {
            uint32_t b1a = sbase + SM_B1 + tq * 64, park = sbase + tid * 16;
#pragma unroll 1
            for (int c = 1; c < 9; c += 2) {
                if (warp == 0) DBG(2 + (c >> 1));
                run_chunk<1>(acc1, acc0, af, 1, bars, desc0, adesc0, b1a, park, nullptr, sig, rbar, lane, rstd0, rstd1);
                run_chunk<1>(acc0, acc1, af, 0, bars, desc0, adesc0, b1a + 256, park + 16384, nullptr, sig, rbar, lane, rstd0, rstd1);
                b1a += 512;
                park += 32768;
            }
        }
        if (warp == 0) DBG(6);
        WG_WAIT(0);
        if (sig) asm volatile("mbarrier.arrive.shared::cluster.b64 _, [%0];" ::"r"(rbar + 5 * 8) : "memory");
        fence_acc(acc0);
#pragma unroll
        for (int k = 0; k < 32; k++)
            asm volatile("ld.shared.v4.b32 {%0,%1,%2,%3}, [%4];"
                         : "=r"(af[k][0]), "=r"(af[k][1]), "=r"(af[k][2]), "=r"(af[k][3])
                         : "r"(sbase + tid * 16 + k * 4096) : "memory");
        {
#pragma unroll
            for (int s = 0; s < 6; s++) {
                mbar_wait(bars + BAR_FULL + s * 8, 1);
                WG_FENCE();
                mma_stage_rt(s, acc1, af, desc0, adesc0);
                WG_COMMIT();
                if (s < 2) epi_gelu(acc0, s, sbase + SM_B1 + tq * 64 + 8 * 256, rstd0, rstd1, af[32 + (s & 1)]);
                if (s == 2 || s == 3) {
                    uint32_t tmp[4];
                    epi_gelu(acc0, s, sbase + SM_B1 + tq * 64 + 8 * 256, rstd0, rstd1, tmp);
                    const int lrow = warp * 16 + (lane & 7) + ((lane >> 3) & 1) * 8;
                    stsm_x4(tmp, sbase + 8 * 16384 + lrow * 128 + (((s * 2 + (lane >> 4)) ^ (lrow & 7)) << 4));
                }
                if (s == 3) {
                    asm volatile("fence.proxy.async.shared::cta;" ::: "memory");
                    asm volatile("bar.sync %0, 128;" ::"r"(3 + wgid) : "memory");
                }
                if (s > 0) {
                    WG_WAIT(1);
                    if (sig) asm volatile("mbarrier.arrive.shared::cluster.b64 _, [%0];" ::"r"(rbar + (s - 1) * 8) : "memory");
                }
                if (s == 5) warp_arrive(bars + BAR_PARKFREE, lane);
            }
        }
        uint4* part = g_part + (size_t)((m * 9 * 8 + warp) * 8 + f) * (4 * 32) + lane;
        uint32_t stored = bars + BAR_STORED;
#pragma unroll 1
        for (int c = 1; c < 9; c += 2) {
            if (warp == 0) DBG(7 + (c >> 1));
            run_chunk<2>(acc0, acc1, af, 0, bars, desc0, adesc0, stored, par, part, sig, rbar, lane, 0.f, 0.f);
            run_chunk<2>(acc1, acc0, af, 1, bars, desc0, adesc0, stored + 8, par, part + 8 * 8 * 4 * 32, sig, rbar, lane, 0.f, 0.f);
            part += 2 * 8 * 8 * 4 * 32;
            stored += 16;
        }
        const int t0 = m * 128 + f * 16 + g;
        asm volatile("griddepcontrol.wait;" ::: "memory");
        const float g0 = __ldcg(&g_gate[t0]), g1 = __ldcg(&g_gate[t0 + 8]);
        WG_WAIT(0);
        fence_acc(acc1);
#pragma unroll
        for (int i = 0; i < 4; i++) epi_part(acc1, i, part, par);
        asm volatile("barrier.cluster.arrive.relaxed.aligned;" ::: "memory");
        if (warp == 0) DBG(11);
        {
            const uint32_t gA = pack_bf16(g0, g0), gB = pack_bf16(g1, g1);
            const uint32_t half2 = 0x3f003f00u, one2 = 0x3f803f80u;
            const uint32_t oA = hsub2_bf(one2, gA), oB = hsub2_bf(one2, gB);
            uint32_t* o32 = reinterpret_cast<uint32_t*>(out + (size_t)t0 * D_MODEL + 2 * tq) + warp * 4;
            const uint32_t lm = sbase + 16384 + (lane & 7) * 32 + ((lane >> 3) & 1) * 16 + warp * 256;
            const uint32_t a0 = sbase + (warp >> 1) * 512 + lane * 16 + (warp & 1) * 8;
            const uint32_t b2a = sbase + SM_B2 + (warp >> 1) * 32 + tq * 8 + (warp & 1) * 4;
            const uint2* ps0 = reinterpret_cast<const uint2*>(
                g_part + (m * 9 * 8 + f) * (8 * 4 * 32) + (warp >> 1) * 32 + lane) + (warp & 1);
            uint2 v[4][8], av[4];
            uint32_t bb[4], bad = 0;
#pragma unroll
            for (int k = 0; k < 4; k++) {
                const int c = NFIN_HELP + k;
                const uint32_t bo = red_buf(c);
                mbar_wait(bars + BAR_LOADED + c * 8, 0);
                if (k < 3) {
#pragma unroll
                    for (int q = 0; q < 8; q++) {
                        v[k][q] = ssm::lds64(a0 + bo + q * 2048);
                        bad |= v[k][q].x ^ par;
                    }
                }
                asm volatile("ldmatrix.sync.aligned.m8n8.x2.trans.shared.b16 {%0,%1}, [%2];"
                             : "=r"(av[k].x), "=r"(av[k].y) : "r"(lm + bo) : "memory");
                bb[k] = ssm::lds32(b2a + c * 128);
            }
            auto emit = [&](int k) {
                const int c = NFIN_HELP + k;
                float sx0 = 0.f, sx1 = 0.f, sy0 = 0.f, sy1 = 0.f;
#pragma unroll
                for (int q = 0; q < 8; q++) {
                    sx0 += bf_lo(v[k][q].x); sx1 += bf_hi(v[k][q].x);
                    sy0 += bf_lo(v[k][q].y); sy1 += bf_hi(v[k][q].y);
                }
                o32[c * 32] = hadd2_bf(hmul2_bf(gA, av[k].x), hmul2_bf(oA, hfma2_bf(pack_bf16(sx0, sx1), half2, bb[k])));
                o32[c * 32 + 4 * D_MODEL] =
                    hadd2_bf(hmul2_bf(gB, av[k].y), hmul2_bf(oB, hfma2_bf(pack_bf16(sy0, sy1), half2, bb[k])));
            };
            auto reload = [&](int k) {
                uint32_t b = 0;
#pragma unroll
                for (int q = 0; q < 8; q++) {
                    unsigned long long w;
                    asm volatile("ld.relaxed.gpu.global.b64 %0, [%1];" : "=l"(w)
                                 : "l"(ps0 + (NFIN_HELP + k) * (8 * 8 * 4 * 32 * 2) + q * 256) : "memory");
                    v[k][q] = make_uint2((uint32_t)w, (uint32_t)(w >> 32));
                    b |= v[k][q].x ^ par;
                }
                return b;
            };
            int tries = 0;
            while (__any_sync(0xffffffffu, bad & 1)) {
                bad = reload(0) | reload(1) | reload(2);
                if (++tries > (1 << 20)) asm volatile("trap;");
            }
            emit(0); emit(1); emit(2);
            if (warp == 0) DBG(32);
            probe_partials(g_part + ((m * 9 + 8) * 8 + f) * (8 * 4 * 32) + (lane & 7) * 128 + (warp >> 1) * 32 + 31, par);
            do {
                bad = reload(3);
                if (++tries > (1 << 20)) asm volatile("trap;");
            } while (__any_sync(0xffffffffu, bad & 1));
            emit(3);
            if (warp == 0) DBG(33);
        }
        asm volatile("barrier.cluster.wait.aligned;" ::: "memory");
        if (warp == 0) DBG(13);
    }
}

typedef CUresult (*EncodeFn)(CUtensorMap*, CUtensorMapDataType, cuuint32_t, void*, const cuuint64_t*,
                             const cuuint64_t*, const cuuint32_t*, const cuuint32_t*, CUtensorMapInterleave,
                             CUtensorMapSwizzle, CUtensorMapL2promotion, CUtensorMapFloatOOBfill);

static void make_map(EncodeFn enc, CUtensorMap* m, const void* ptr, uint64_t cols, uint64_t rows, uint32_t box_c,
                     uint32_t box_r, CUtensorMapSwizzle swz = CU_TENSOR_MAP_SWIZZLE_128B) {
    cuuint64_t dim[2] = {cols, rows};
    cuuint64_t str[1] = {cols * 2};
    cuuint32_t box[2] = {box_c, box_r};
    cuuint32_t es[2] = {1, 1};
    enc(m, CU_TENSOR_MAP_DATA_TYPE_BFLOAT16, 2, const_cast<void*>(ptr), dim, str, box, es,
        CU_TENSOR_MAP_INTERLEAVE_NONE, swz, CU_TENSOR_MAP_L2_PROMOTION_L2_128B,
        CU_TENSOR_MAP_FLOAT_OOB_FILL_NONE);
}

}

extern "C" void kernel_launch(void* const* d_in, const int* in_sizes, int n_in, void* d_out, int out_size) {
    const bf16* u = (const bf16*)d_in[0];
    const bf16* A_re = (const bf16*)d_in[1];
    const bf16* A_im = (const bf16*)d_in[2];
    const bf16* B_re = (const bf16*)d_in[3];
    const bf16* B_im = (const bf16*)d_in[4];
    const bf16* C_re = (const bf16*)d_in[5];
    const bf16* C_im = (const bf16*)d_in[6];
    const bf16* log_dt = (const bf16*)d_in[7];
    const bf16* Dskip = (const bf16*)d_in[8];
    const bf16* w1 = (const bf16*)d_in[10];
    const bf16* b1 = (const bf16*)d_in[11];
    const bf16* w2 = (const bf16*)d_in[12];
    const bf16* b2 = (const bf16*)d_in[13];
    const bf16* gw = (const bf16*)d_in[14];
    bf16* out = (bf16*)d_out;

    static EncodeFn enc = nullptr;
    if (!enc) {
        void* fn = nullptr;
        cudaDriverEntryPointQueryResult q;
        cudaGetDriverEntryPoint("cuTensorMapEncodeTiled", &fn, cudaEnableDefault, &q);
        enc = (EncodeFn)fn;
        cudaFuncSetAttribute(mlp_kernel, cudaFuncAttributeMaxDynamicSharedMemorySize, MLP_SMEM);
        cudaFuncSetAttribute(ssm::ssm_kernel, cudaFuncAttributeMaxDynamicSharedMemorySize, ssm::K1_SMEM);
    }
    static void* aT_ptr = nullptr;
    if (!aT_ptr) cudaGetSymbolAddress(&aT_ptr, g_aT);
    CUtensorMap tmx, tmw1, tmw2, tma;
    make_map(enc, &tma, aT_ptr, L_SEQ, D_MODEL, 16, 64, CU_TENSOR_MAP_SWIZZLE_NONE);
    make_map(enc, &tmx, u, D_MODEL, L_SEQ, 64, 128);
    make_map(enc, &tmw1, w1, F_DIM, D_MODEL, 64, 48);
    make_map(enc, &tmw2, w2, D_MODEL, F_DIM, 64, 48);

    cudaStream_t st = cudaStreamPerThread;
    ssm::Params sp{A_re, A_im, B_re, B_im, C_re, C_im, log_dt, Dskip};
    CUtensorMap tmc, tmo;
    make_map(enc, &tmc, u, D_MODEL, L_SEQ, 8, 256, CU_TENSOR_MAP_SWIZZLE_NONE);
    make_map(enc, &tmo, aT_ptr, 64, D_MODEL * 32, 64, 32);
    ssm::ssm_kernel<<<ssm::K1_CTAS + ssm::K1_STAT, 128 * ssm::K1_WGS, ssm::K1_SMEM, st>>>(tmc, tmo, u, gw, sp);
    cudaLaunchConfig_t cfg = {};
    cfg.gridDim = dim3(128);
    cfg.blockDim = dim3(384);
    cfg.dynamicSmemBytes = MLP_SMEM;
    cfg.stream = st;
    cudaLaunchAttribute at[1];
    at[0].id = cudaLaunchAttributeProgrammaticStreamSerialization;
    at[0].val.programmaticStreamSerializationAllowed = 1;
    cfg.attrs = at;
    cfg.numAttrs = 1;
    cudaLaunchKernelEx(&cfg, mlp_kernel, tmx, tmw1, tmw2, tma, b1, b2, out);
}
```

```cpp
#include <cuda_runtime.h>
#include <cuda_bf16.h>
#include <cuda.h>
#include <stdint.h>

namespace {

constexpr int L_SEQ = 2048;
constexpr int D_MODEL = 576;
constexpr int F_DIM = 4608;
constexpr int N_MODES = 128;

typedef __nv_bfloat16 bf16;

__device__ uint2 g_rowstat[L_SEQ];
__device__ float g_gate[L_SEQ];
__device__ bf16 g_aT[D_MODEL * L_SEQ];
__device__ uint4 g_part[16 * 9 * 8 * 8 * 4 * 32];
__device__ unsigned g_stat_epoch[16];
__device__ unsigned g_epoch;

#define DBG(slot)
#define DBG1(slot)

__device__ __forceinline__ uint32_t smem_u32(const void* p) { return (uint32_t)__cvta_generic_to_shared(p); }
__device__ __forceinline__ float bf16r(float x) { return __bfloat162float(__float2bfloat16_rn(x)); }
__device__ __forceinline__ uint32_t pack_bf16(float lo, float hi) {
    uint32_t r;
    asm("cvt.rn.bf16x2.f32 %0, %1, %2;" : "=r"(r) : "f"(hi), "f"(lo));
    return r;
}
__device__ __forceinline__ float bf_lo(uint32_t v) { return __uint_as_float(v << 16); }
__device__ __forceinline__ float bf_hi(uint32_t v) { return __uint_as_float(v & 0xffff0000u); }

__device__ __forceinline__ void mbar_init(uint32_t bar, int cnt) {
    asm volatile("mbarrier.init.shared::cta.b64 [%0], %1;" ::"r"(bar), "r"(cnt));
}
__device__ __forceinline__ void mbar_expect(uint32_t bar, int bytes) {
    asm volatile("mbarrier.arrive.expect_tx.shared::cta.b64 _, [%0], %1;" ::"r"(bar), "r"(bytes) : "memory");
}
__device__ __forceinline__ void mbar_wait(uint32_t bar, int parity) {
    asm volatile(
        "{\n.reg .pred p;\n.reg .u32 n;\nmov.u32 n, 0;\n"
        "WAIT_LOOP:\n"
        "mbarrier.try_wait.parity.shared::cta.b64 p, [%0], %1;\n"
        "@p bra WAIT_DONE;\n"
        "add.u32 n, n, 1;\n"
        "setp.lt.u32 p, n, 4194304;\n"
        "@p bra WAIT_LOOP;\n"
        "trap;\n"
        "WAIT_DONE:\n}\n" ::"r"(bar), "r"(parity) : "memory");
}
__device__ __forceinline__ void tma2d(uint32_t dst, const CUtensorMap* m, int c0, int c1, uint32_t bar) {
    asm volatile(
        "cp.async.bulk.tensor.2d.shared::cluster.global.mbarrier::complete_tx::bytes [%0], [%1, {%3,%4}], [%2];"
        ::"r"(dst), "l"(m), "r"(bar), "r"(c0), "r"(c1) : "memory");
}
__device__ __forceinline__ void tma2d_mc(uint32_t dst, const CUtensorMap* m, int c0, int c1, uint32_t bar,
                                         uint16_t mask) {
    asm volatile(
        "cp.async.bulk.tensor.2d.shared::cluster.global.mbarrier::complete_tx::bytes.multicast::cluster.L2::cache_hint "
        "[%0], [%1, {%3,%4}], [%2], %5, %6;"
        ::"r"(dst), "l"(m), "r"(bar), "r"(c0), "r"(c1), "h"(mask), "l"(0x12F0000000000000ull) : "memory");
}
__device__ __forceinline__ void ldsm_x4(uint32_t (&r)[4], uint32_t addr) {
    asm volatile("ldmatrix.sync.aligned.m8n8.x4.shared.b16 {%0,%1,%2,%3}, [%4];"
                 : "=r"(r[0]), "=r"(r[1]), "=r"(r[2]), "=r"(r[3]) : "r"(addr) : "memory");
}
#define WG_FENCE() asm volatile("wgmma.fence.sync.aligned;\n" ::: "memory")
#define WG_COMMIT() asm volatile("wgmma.commit_group.sync.aligned;\n" ::: "memory")
#define WG_WAIT(n) asm volatile("wgmma.wait_group.sync.aligned %0;\n" ::"n"(n) : "memory")

template <int SCALE_D, int OFF>
__device__ __forceinline__ void wgmma_rs_n64(float (&d)[32], const uint32_t (&a)[4], uint32_t desc_lo) {
    asm volatile(
        "{\n.reg .pred p;\n.reg .b32 lo;\n.reg .b64 dsc;\nsetp.ne.b32 p, %37, 0;\n"
        "add.u32 lo, %36, %38;\nmov.b64 dsc, {lo, 0x40000040};\n"
        "wgmma.mma_async.sync.aligned.m64n64k16.f32.bf16.bf16 "
        "{%0,%1,%2,%3,%4,%5,%6,%7,%8,%9,%10,%11,%12,%13,%14,%15,%16,%17,%18,%19,%20,%21,%22,%23,%24,%25,%26,%27,%28,%29,%30,%31},"
        "{%32,%33,%34,%35}, dsc, p, 1, 1, 1;\n}\n"
        : "+f"(d[0]), "+f"(d[1]), "+f"(d[2]), "+f"(d[3]), "+f"(d[4]), "+f"(d[5]), "+f"(d[6]), "+f"(d[7]),
          "+f"(d[8]), "+f"(d[9]), "+f"(d[10]), "+f"(d[11]), "+f"(d[12]), "+f"(d[13]), "+f"(d[14]), "+f"(d[15]),
          "+f"(d[16]), "+f"(d[17]), "+f"(d[18]), "+f"(d[19]), "+f"(d[20]), "+f"(d[21]), "+f"(d[22]), "+f"(d[23]),
          "+f"(d[24]), "+f"(d[25]), "+f"(d[26]), "+f"(d[27]), "+f"(d[28]), "+f"(d[29]), "+f"(d[30]), "+f"(d[31])
        : "r"(a[0]), "r"(a[1]), "r"(a[2]), "r"(a[3]), "r"(desc_lo), "n"(SCALE_D), "n"(OFF));
}
template <int OFF, int AOFF>
__device__ __forceinline__ void wgmma_ss_n64(float (&d)[32], uint32_t adesc_lo, uint32_t desc_lo) {
    asm volatile(
        "{\n.reg .pred p;\n.reg .b32 lo;\n.reg .b64 dsc, dsa;\nsetp.ne.b32 p, 1, 0;\n"
        "add.u32 lo, %33, %34;\nmov.b64 dsc, {lo, 0x40000040};\n"
        "add.u32 lo, %32, %35;\nmov.b64 dsa, {lo, 0x40000040};\n"
        "wgmma.mma_async.sync.aligned.m64n64k16.f32.bf16.bf16 "
        "{%0,%1,%2,%3,%4,%5,%6,%7,%8,%9,%10,%11,%12,%13,%14,%15,%16,%17,%18,%19,%20,%21,%22,%23,%24,%25,%26,%27,%28,%29,%30,%31},"
        "dsa, dsc, p, 1, 1, 0, 1;\n}\n"
        : "+f"(d[0]), "+f"(d[1]), "+f"(d[2]), "+f"(d[3]), "+f"(d[4]), "+f"(d[5]), "+f"(d[6]), "+f"(d[7]),
          "+f"(d[8]), "+f"(d[9]), "+f"(d[10]), "+f"(d[11]), "+f"(d[12]), "+f"(d[13]), "+f"(d[14]), "+f"(d[15]),
          "+f"(d[16]), "+f"(d[17]), "+f"(d[18]), "+f"(d[19]), "+f"(d[20]), "+f"(d[21]), "+f"(d[22]), "+f"(d[23]),
          "+f"(d[24]), "+f"(d[25]), "+f"(d[26]), "+f"(d[27]), "+f"(d[28]), "+f"(d[29]), "+f"(d[30]), "+f"(d[31])
        : "r"(adesc_lo), "r"(desc_lo), "n"(OFF), "n"(AOFF));
}
constexpr int NAF = 34;
template <int S, int FIRST>
__device__ __forceinline__ void mma_stage(float (&d)[32], const uint32_t (&af)[NAF][4], uint32_t desc_lo,
                                          uint32_t adesc_lo) {
    constexpr int B = (S * 96 * 128) >> 4;
    wgmma_rs_n64<FIRST ? 0 : 1, B + 0 * 128>(d, af[S * 6 + 0], desc_lo);
    wgmma_rs_n64<1, B + 1 * 128>(d, af[S * 6 + 1], desc_lo);
    wgmma_rs_n64<1, B + 2 * 128>(d, af[S * 6 + 2], desc_lo);
    wgmma_rs_n64<1, B + 3 * 128>(d, af[S * 6 + 3], desc_lo);
    if constexpr (S < 5) {
        wgmma_rs_n64<1, B + 4 * 128>(d, af[S * 6 + 4], desc_lo);
        wgmma_rs_n64<1, B + 5 * 128>(d, af[S * 6 + 5], desc_lo);
    } else {
        wgmma_ss_n64<B + 4 * 128, 4>(d, adesc_lo, desc_lo);
        wgmma_ss_n64<B + 5 * 128, 6>(d, adesc_lo, desc_lo);
    }
}
__device__ __forceinline__ void mma_stage_rt(int s, float (&d)[32], const uint32_t (&af)[NAF][4], uint32_t desc_lo,
                                             uint32_t adesc_lo) {
    if (s == 0) mma_stage<0, 1>(d, af, desc_lo, adesc_lo);
    if (s == 1) mma_stage<1, 0>(d, af, desc_lo, adesc_lo);
    if (s == 2) mma_stage<2, 0>(d, af, desc_lo, adesc_lo);
    if (s == 3) mma_stage<3, 0>(d, af, desc_lo, adesc_lo);
    if (s == 4) mma_stage<4, 0>(d, af, desc_lo, adesc_lo);
    if (s == 5) mma_stage<5, 0>(d, af, desc_lo, adesc_lo);
}
__device__ __forceinline__ void stsm_x4(const uint32_t (&r)[4], uint32_t addr) {
    asm volatile("stmatrix.sync.aligned.m8n8.x4.shared.b16 [%4], {%0,%1,%2,%3};"
                 ::"r"(r[0]), "r"(r[1]), "r"(r[2]), "r"(r[3]), "r"(addr) : "memory");
}
__device__ __forceinline__ void fence_acc(float (&d)[32]) {
#pragma unroll
    for (int i = 0; i < 32; i++) asm volatile("" : "+f"(d[i])::"memory");
}

__device__ __forceinline__ uint32_t hadd2_bf(uint32_t a, uint32_t b) {
    uint32_t r;
    asm("add.rn.bf16x2 %0, %1, %2;" : "=r"(r) : "r"(a), "r"(b));
    return r;
}
__device__ __forceinline__ uint32_t hsub2_bf(uint32_t a, uint32_t b) {
    uint32_t r;
    asm("sub.rn.bf16x2 %0, %1, %2;" : "=r"(r) : "r"(a), "r"(b));
    return r;
}
__device__ __forceinline__ uint32_t hmul2_bf(uint32_t a, uint32_t b) {
    uint32_t r;
    asm("mul.rn.bf16x2 %0, %1, %2;" : "=r"(r) : "r"(a), "r"(b));
    return r;
}
__device__ __forceinline__ uint32_t hfma2_bf(uint32_t a, uint32_t b, uint32_t c) {
    uint32_t r;
    asm("fma.rn.bf16x2 %0, %1, %2, %3;" : "=r"(r) : "r"(a), "r"(b), "r"(c));
    return r;
}
namespace ssm {
constexpr int O_H = 0;
constexpr int O_L = 12288;
constexpr int HL_END = O_L + 16384;
constexpr int O_Q = 0;
constexpr int O_Q12 = 5120;
constexpr int O_Q34 = O_Q12 + 1280;
constexpr int O_Y12 = O_Q34 + 2048 - 2176;
constexpr int O_Y34 = O_Y12 + 8704 - 4352;
constexpr int O_W3 = O_Y34 + 8704 + 256;
constexpr int O_W4 = O_W3 + 2048 + 256;
constexpr int O_W5 = O_W4 + 2048;
constexpr int O_U = HL_END;
constexpr int O_RAW = O_U + 6144;
constexpr int O_W1 = O_U + 6144 + 256;
constexpr int O_W2 = O_W1 + 3072 + 256;
constexpr int O_ST = O_RAW;
constexpr int O_KN = O_W2 + 3072;
constexpr int O_A12 = O_KN + 1344;
constexpr int O_A3 = O_A12 + 384;
constexpr int O_KQ = O_A3 + 304;
constexpr int WG_BYTES = 44032;
static_assert(O_W5 + 2048 <= HL_END && O_KQ + 16 <= WG_BYTES && WG_BYTES % 1024 == 0 && O_RAW + 8192 <= WG_BYTES, "map");

struct cplx { float r, i; };
__device__ __forceinline__ cplx cmul(cplx a, cplx b) {
    cplx o;
    o.r = fmaf(a.r, b.r, -a.i * b.i);
    o.i = fmaf(a.r, b.i, a.i * b.r);
    return o;
}
__device__ __forceinline__ cplx cexp_l(float lr, float li, float l) {
    const float e = exp2f((lr * l) * 1.4426950408889634f);
    const float ang = li * l;
    const float k = rintf(ang * 0.15915494309189535f);
    float r = fmaf(k, -6.2831854820251465f, ang);
    r = fmaf(k, 1.7484556000744487e-07f, r);
    cplx o;
    o.r = e * __cosf(r);
    o.i = e * __sinf(r);
    return o;
}
template <typename T> __device__ __forceinline__ T* sp(uint32_t a) {
    return reinterpret_cast<T*>(__cvta_shared_to_generic(a));
}
__device__ __forceinline__ void sts32(uint32_t a, uint32_t v) { *sp<uint32_t>(a) = v; }
__device__ __forceinline__ void sts16(uint32_t a, uint32_t v) { *sp<unsigned short>(a) = (unsigned short)v; }
__device__ __forceinline__ uint32_t lds16(uint32_t a) { return *sp<unsigned short>(a); }
__device__ __forceinline__ uint32_t lds32(uint32_t a) { return *sp<uint32_t>(a); }
__device__ __forceinline__ float ldsf(uint32_t a) { return *sp<float>(a); }
__device__ __forceinline__ uint2 lds64(uint32_t a) { return *sp<uint2>(a); }
__device__ __forceinline__ void sts64(uint32_t a, uint32_t x, uint32_t y) { *sp<uint2>(a) = make_uint2(x, y); }
__device__ __forceinline__ void sts64f(uint32_t a, float x, float y) { *sp<float2>(a) = make_float2(x, y); }
__device__ __forceinline__ void sts128(uint32_t a, uint32_t x, uint32_t y, uint32_t z, uint32_t w) {
    *sp<uint4>(a) = make_uint4(x, y, z, w);
}
__device__ __forceinline__ uint4 lds128(uint32_t a) { return *sp<uint4>(a); }
__device__ __forceinline__ void wg_bar(int id) { asm volatile("bar.sync %0, 128;" ::"r"(id) : "memory"); }
__device__ __forceinline__ uint32_t u_addr(uint32_t sb, int grp) {
    const int gq = grp + 128;
    return sb + O_U + (gq >> 3) * 128 + (((gq ^ (gq >> 3)) & 7) << 4);
}
template <int SCALE_D, int OA, int OB>
__device__ __forceinline__ void wgmma_ss_n32(float (&d)[16], uint32_t dl) {
    asm volatile(
        "{\n.reg .pred p;\n.reg .b32 lo;\n.reg .b64 x, y;\nsetp.ne.b32 p, %17, 0;\n"
        "add.u32 lo, %16, %18;\nmov.b64 x, {lo, 0x40000040};\nadd.u32 lo, %16, %19;\nmov.b64 y, {lo, 0x40000040};\n"
        "wgmma.mma_async.sync.aligned.m64n32k16.f32.bf16.bf16 "
        "{%0,%1,%2,%3,%4,%5,%6,%7,%8,%9,%10,%11,%12,%13,%14,%15}, x, y, p, 1, 1, 0, 0;\n}\n"
        : "+f"(d[0]), "+f"(d[1]), "+f"(d[2]), "+f"(d[3]), "+f"(d[4]), "+f"(d[5]), "+f"(d[6]), "+f"(d[7]),
          "+f"(d[8]), "+f"(d[9]), "+f"(d[10]), "+f"(d[11]), "+f"(d[12]), "+f"(d[13]), "+f"(d[14]), "+f"(d[15])
        : "r"(dl), "n"(SCALE_D), "n"(OA), "n"(OB));
}
template <int OB>
__device__ __forceinline__ void wgmma_rs_n32(float (&d)[16], uint32_t a0, uint32_t a1, uint32_t a2, uint32_t a3,
                                             uint32_t dl) {
    asm volatile(
        "{\n.reg .pred p;\n.reg .b32 lo;\n.reg .b64 y;\nsetp.ne.b32 p, 1, 0;\n"
        "add.u32 lo, %20, %21;\nmov.b64 y, {lo, 0x40000040};\n"
        "wgmma.mma_async.sync.aligned.m64n32k16.f32.bf16.bf16 "
        "{%0,%1,%2,%3,%4,%5,%6,%7,%8,%9,%10,%11,%12,%13,%14,%15}, {%16,%17,%18,%19}, y, p, 1, 1, 0;\n}\n"
        : "+f"(d[0]), "+f"(d[1]), "+f"(d[2]), "+f"(d[3]), "+f"(d[4]), "+f"(d[5]), "+f"(d[6]), "+f"(d[7]),
          "+f"(d[8]), "+f"(d[9]), "+f"(d[10]), "+f"(d[11]), "+f"(d[12]), "+f"(d[13]), "+f"(d[14]), "+f"(d[15])
        : "r"(a0), "r"(a1), "r"(a2), "r"(a3), "r"(dl), "n"(OB));
}
template <int KS> struct KgenSteps {
    static __device__ __forceinline__ void run(float (&d)[16], uint32_t dl) {
        KgenSteps<KS - 1>::run(d, dl);
        constexpr int k = KS - 1;
        wgmma_ss_n32<(k > 0), (O_H + (k / 4) * 3072 + (k % 4) * 32) / 16, (O_L + (k / 4) * 4096 + (k % 4) * 32) / 16>(d, dl);
    }
};
template <> struct KgenSteps<0> { static __device__ __forceinline__ void run(float (&)[16], uint32_t) {} };
template <int K0, int N, int I> struct NearSteps {
    static __device__ __forceinline__ void run(float (&d)[16], const uint4 (&f)[N], uint32_t dl) {
        NearSteps<K0, N, I - 1>::run(d, f, dl);
        constexpr int k = K0 + I - 1, dd = k / 4, kk = 4 * dd - (k - 3);
        wgmma_rs_n32<(O_U + (16 - dd) * 128 + kk * 32) / 16>(d, f[I - 1].x, f[I - 1].y, f[I - 1].z, f[I - 1].w, dl);
    }
};
template <int K0, int N> struct NearSteps<K0, N, 0> {
    static __device__ __forceinline__ void run(float (&)[16], const uint4 (&)[N], uint32_t) {}
};
template <int N>
__device__ __forceinline__ void load_toep(uint4 (&f)[N], uint32_t addr, uint32_t& prev) {
#pragma unroll
    for (int k = 0; k < N; k++)
    { const uint2 v = lds64(addr + k * 128); f[k].x = v.x; f[k].y = v.y; }
#pragma unroll
    for (int k = 0; k < N; k++) {
        f[k].z = prev;
        f[k].w = f[k].x;
        prev = f[k].y;
    }
}
__device__ __forceinline__ void mma16816(float (&d)[4], uint32_t a0, uint32_t a1, uint32_t a2, uint32_t b0,
                                         uint32_t b1) {
    asm("mma.sync.aligned.m16n8k16.row.col.f32.bf16.bf16.f32 {%0,%1,%2,%3}, {%4,%5,%6,%4}, {%7,%8}, {%0,%1,%2,%3};"
                 : "+f"(d[0]), "+f"(d[1]), "+f"(d[2]), "+f"(d[3])
                 : "r"(a0), "r"(a1), "r"(a2), "r"(b0), "r"(b1));
}
__device__ __forceinline__ uint4 ldsm_x4_t(uint32_t addr) {
    uint4 r;
    asm volatile("ldmatrix.sync.aligned.m8n8.x4.trans.shared.b16 {%0,%1,%2,%3}, [%4];"
                 : "=r"(r.x), "=r"(r.y), "=r"(r.z), "=r"(r.w) : "r"(addr));
    return r;
}
struct Params { const bf16 *A_re, *A_im, *B_re, *B_im, *C_re, *C_im, *log_dt, *Dskip; };
struct ModeIn { float ar, ai, br, bi, cr, ci, ldt, dsk; };
__device__ __forceinline__ ModeIn load_mode(const Params& p, int d, int n) {
    ModeIn m;
    const int i = d * N_MODES + n;
    m.ar = __bfloat162float(p.A_re[i]); m.ai = __bfloat162float(p.A_im[i]);
    m.br = __bfloat162float(p.B_re[i]); m.bi = __bfloat162float(p.B_im[i]);
    m.cr = __bfloat162float(p.C_re[i]); m.ci = __bfloat162float(p.C_im[i]);
    m.ldt = __bfloat162float(p.log_dt[d]); m.dsk = __bfloat162float(p.Dskip[d]);
    return m;
}

__device__ __forceinline__ void gen_powers(const ModeIn& mi, uint32_t sb, int t) {
    const float dt = bf16r(expf(mi.ldt));
    const float lr = dt * mi.ar, li = dt * mi.ai;
    const float br = dt * mi.br, bi = dt * mi.bi;
    cplx c;
    c.r = mi.cr * br - mi.ci * bi;
    c.i = mi.cr * bi + mi.ci * br;
    const cplx z = cexp_l(lr, li, 1.f), wv = cexp_l(lr, li, 8.f), Z = cexp_l(lr, li, 256.f);
    const cplx z2 = cmul(z, z), z4 = cmul(z2, z2);
    const uint32_t x0 = ((t & 31) >> 2) * 16 + (t & 3) * 4;
    uint32_t xs[8];
#pragma unroll
    for (int j = 0; j < 8; j++) xs[j] = sb + (x0 ^ (j << 4));
    const uint32_t ho = O_H + (t >> 5) * 3072, lo_ = O_L + (t >> 5) * 4096;
#define PUT_H(row, v) sts32(xs[(row) & 7] + ho + (row) * 128, pack_bf16((v).r, -(v).i))
#define PUT_L(row, v) sts32(xs[(row) & 7] + lo_ + (row) * 128, pack_bf16((v).r, (v).i))
    cplx h = c;
    PUT_H(0, h);
#pragma unroll
    for (int k = 1; k < 8; k++) { h = cmul(h, z); PUT_H(k, h); }
    cplx hz = cmul(c, Z);
    PUT_H(8, hz);
    { cplx a = cmul(hz, z2); PUT_H(9, a); a = cmul(hz, z4); PUT_H(10, a); a = cmul(a, z2); PUT_H(11, a); }
    hz = cmul(hz, Z); PUT_H(12, hz);
    { cplx a = cmul(hz, z4); PUT_H(13, a); }
    hz = cmul(hz, Z); PUT_H(14, hz);
    { cplx a = cmul(hz, z4); PUT_H(15, a); }
#pragma unroll
    for (int k = 16; k < 21; k++) { hz = cmul(hz, Z); PUT_H(k, hz); }
    const cplx w2 = cmul(wv, wv);
    cplx le, lo = wv;
    le.r = 1.f; le.i = 0.f;
    uint32_t lb = lo_;
#pragma unroll 1
    for (int kb = 0; kb < 4; kb++) {
#pragma unroll
        for (int k = 0; k < 8; k += 2) {
            sts32(xs[k] + lb + k * 128, pack_bf16(le.r, le.i));
            sts32(xs[k + 1] + lb + (k + 1) * 128, pack_bf16(lo.r, lo.i));
            le = cmul(le, w2); lo = cmul(lo, w2);
        }
        lb += 1024;
    }
}

__device__ __forceinline__ uint4 pack8(const float (&v)[8]) {
    return make_uint4(pack_bf16(v[0], v[1]), pack_bf16(v[2], v[3]), pack_bf16(v[4], v[5]), pack_bf16(v[6], v[7]));
}
__device__ __forceinline__ void st16B(uint32_t a, const uint4& v) { *sp<uint4>(a) = v; }

__device__ __forceinline__ void build_windows(uint32_t sb, int t) {
    if (t < 64) {
        const int which = t >> 4;
        sts128(sb + (which == 0 ? O_W1 : which == 1 ? O_W2 : which == 2 ? O_W3 : O_W4) - 256 + (t & 15) * 16, 0, 0, 0, 0);
    }
#pragma unroll
    for (int r = 0; r < 2; r++) {
        const int grp = t + r * 128;
        if (grp < 192) {
            const uint4 c0 = lds128(u_addr(sb, grp - 2)), c1 = lds128(u_addr(sb, grp - 1)), c2 = lds128(u_addr(sb, grp));
            float v[24];
            const uint32_t ww[12] = {c0.x, c0.y, c0.z, c0.w, c1.x, c1.y, c1.z, c1.w, c2.x, c2.y, c2.z, c2.w};
#pragma unroll
            for (int i = 2; i < 11; i++) { v[2 * i] = bf_lo(ww[i]); v[2 * i + 1] = bf_hi(ww[i]); }
            float p2[15];
#pragma unroll
            for (int j = 0; j < 15; j++) p2[j] = v[5 + j] + v[6 + j];
            float b1[8], b2[8];
#pragma unroll
            for (int i = 0; i < 8; i++) {
                b2[i] = p2[i + 6] + v[13 + i];
                b1[i] = p2[i + 1] + p2[i + 3] + v[10 + i];
            }
            st16B(sb + O_W1 + grp * 16, pack8(b1));
            st16B(sb + O_W2 + grp * 16, pack8(b2));
            if (r == 0) {
                float b3[8], b5[8];
#pragma unroll
                for (int i = 0; i < 8; i++) {
                    b3[i] = b1[i] + v[11 + i] + v[5 + i];
                    b5[i] = p2[i + 7];
                }
                st16B(sb + O_W3 + grp * 16, pack8(b3));
                st16B(sb + O_W5 + grp * 16, pack8(b5));
                st16B(sb + O_W4 + grp * 16, make_uint4(hadd2_bf(ww[6], ww[2]), hadd2_bf(ww[7], ww[3]),
                                                       hadd2_bf(ww[8], ww[4]), hadd2_bf(ww[9], ww[5])));
            }
        }
    }
}

__device__ __forceinline__ void build_tables(float (&kd)[16], float dskip, uint32_t sb, int t, int bar) {
    const int lane = t & 31, w = t >> 5, g = lane >> 2, tq = lane & 3;
    if (w == 0) {
        if (lane == 0) kd[0] += dskip;
        const uint32_t kn = sb + O_KN + 128;
#pragma unroll
        for (int j = 0; j < 4; j++) {
            const int lo = 8 * j + 2 * tq;
            const uint32_t p0 = pack_bf16(kd[4 * j], kd[4 * j + 1]), p1 = pack_bf16(kd[4 * j + 2], kd[4 * j + 3]);
            sts16(kn + (g + 8 * lo) * 2, p0);
            sts16(kn + (g + 8 * lo + 8) * 2, p0 >> 16);
            if (g < 4) {
#pragma unroll
                for (int e = 0; e < 2; e++) {
                    const uint32_t val = e ? (p1 >> 16) : p1, ad = kn + (256 + 2 * g + 8 * (lo + e)) * 2;
                    sts16(ad, val);
                    if (!(g & 1)) {
                        sts16(ad + 2, val);
                        if (g + lo + e > 0) sts16(ad - 2, val);
                    }
                }
            } else {
#pragma unroll
                for (int e = 0; e < 2; e++) {
                    const uint32_t val = e ? (p1 >> 16) : p1;
                    const int i8 = 64 + (g >= 6 ? 32 : 0) + lo + e;
                    if (j > 0 || i8 >= 66) {
                        sts16(sb + O_A12 + (i8 - 48) * 4 - ((g & 1) ? 0 : 2), val);
                    } else if (g & 1) {
                        sts16(kn + (8 * i8 + 3) * 2, val); sts16(kn + (8 * i8 + 4) * 2, val); sts16(kn + (8 * i8 + 5) * 2, val);
                    } else {
#pragma unroll
                        for (int dd = -2; dd <= 2; dd++)
                            if (i8 == 65 || dd >= -1) sts16(kn + (8 * i8 + dd) * 2, val);
                    }
                }
            }
        }
    } else if (w == 1) {
        if (g < 4) {
#pragma unroll
            for (int j = 0; j < 4; j++) {
                const int i8 = 128 + 32 * g + 8 * j + 2 * tq;
                const uint32_t p0 = pack_bf16(kd[4 * j], kd[4 * j + 1]);
                if (i8 == 128) { sts16(sb + O_A12 + (127 - 48) * 4 + 2, p0); sts16(sb + O_KQ, p0); }
                else sts16(sb + O_A3 + (i8 - 1 - 112) * 2, p0);
                sts16(sb + O_A3 + (i8 - 112) * 2, p0 >> 16);
            }
        } else if (lane == 16) {
            sts16(sb + O_A3 + (255 - 112) * 2, pack_bf16(kd[0], 0.f));
        }
    }
    wg_bar(bar);
    DBG1(4);
    {
#pragma unroll
        for (int r = 0; r < 2; r++) {
            const int i = t + r * 128;
            if (i < 160) {
                const uint32_t ka = sb + O_KN + (4 * i + 8) * 2;
                const uint32_t wm = lds32(ka - 4), w3 = lds32(ka + 12);
                const uint2 wa = lds64(ka), wb = lds64(ka + 16);
                const uint32_t w0 = wa.x, w1 = wa.y, w4 = wb.x, w5 = wb.y;
                sts128(sb + O_Q + i * 32, __byte_perm(w0, wm, 0x7610), __byte_perm(w4, w3, 0x7610),
                       __byte_perm(w0, w0, 0x1032), __byte_perm(w4, w4, 0x1032));
                sts128(sb + O_Q + i * 32 + 16, __byte_perm(w1, w0, 0x7610), __byte_perm(w5, w4, 0x7610),
                       __byte_perm(w1, w1, 0x1032), __byte_perm(w5, w5, 0x1032));
            }
        }
        {
            const uint32_t aa = sb + O_A3 + (8 + t) * 2;
            const uint32_t p0 = lds16(aa) | (lds16(aa - 2) << 16), p1 = lds16(aa + 16) | (lds16(aa + 14) << 16);
            const uint32_t msk = (t & 1) ? 0x0000ffffu : 0xffff0000u;
            sts128(sb + O_Q34 + t * 16, p0, p1, p0 & msk, p1 & msk);
        }
        if (t >= 48) {
            const uint32_t aa = sb + O_A12 + (t - 48 + 8) * 4;
            const uint32_t e0 = lds32(aa), e1 = lds32(aa - 4), f0 = lds32(aa + 32), f1 = lds32(aa + 28);
            sts128(sb + O_Q12 + (t - 48) * 16, __byte_perm(e0, e1, 0x7632), __byte_perm(f0, f1, 0x7632),
                   __byte_perm(e0, e1, 0x5410), __byte_perm(f0, f1, 0x5410));
        }
    }
}

__device__ __forceinline__ void convolve(int d, uint32_t sb, int t, int bar, const CUtensorMap* tmo) {
    const int lane = t & 31, w = t >> 5, g = lane >> 2, tq = lane & 3;
    const uint32_t dl = (sb & 0x3FFFF) >> 4;
    float y[16];
#pragma unroll
    for (int i = 0; i < 16; i++) y[i] = 0.f;
#pragma unroll 1
    for (int step = 0; step < 2; step++) {
    if ((step ^ bar) & 1) {
        const uint32_t qa = sb + O_Q + (16 * w + g - 2 * tq + 56 - 48) * 8;
        uint32_t prev = 0;
        uint32_t qp = qa, du = dl;
#pragma unroll 1
        for (int jj = 0; jj < 4; jj++) {
            uint4 F[8];
            load_toep<8>(F, qp, prev);
            WG_FENCE();
            NearSteps<0, 8, 8>::run(y, F, du);
            WG_COMMIT();
            WG_WAIT(0);
            qp += 8 * 128;
            du -= 16;
        }
        uint4 FC[5];
        load_toep<5>(FC, qp, prev);
        WG_FENCE();
        NearSteps<0, 5, 5>::run(y, FC, du);
        WG_COMMIT();
        WG_WAIT(0);
#pragma unroll
        for (int i = 0; i < 16; i++) asm volatile("" : "+f"(y[i])::"memory");
    } else {
        const int par = w & 1;
        const uint32_t qoff = sb + (g - 2 * tq) * 16;
        const uint32_t roff = sb + (lane & 15) * 16 + par * 256;
        const uint32_t yoff = sb + (136 * par + 8 * g + 2 * tq) * 4;
        if (w < 2) {
            const uint32_t wb = roff + ((lane >> 4) ? O_W2 : O_W1);
            uint4 f[5];
#pragma unroll
            for (int q = 4; q <= 8; q++) f[q - 4] = lds128(qoff + O_Q12 + (16 * q - 56) * 16);
            uint4 bt[12];
#pragma unroll
            for (int i = 0; i < 6; i++) {
                if (i == 0) bt[0] = ldsm_x4_t(wb - 256);
                bt[2 * i + 1] = ldsm_x4_t(wb + (2 * i) * 256);
                if (i > 0) bt[2 * i] = ldsm_x4_t(wb + (2 * i - 1) * 256);
                float a0[4] = {0.f, 0.f, 0.f, 0.f}, a1[4] = {0.f, 0.f, 0.f, 0.f};
#pragma unroll
                for (int q = 4; q <= 8; q++) {
                    const int k = 2 * i + 4 - q;
                    if (k >= -1) {
                        mma16816(a0, f[q - 4].x, f[q - 4].y, q > 4 ? f[q > 4 ? q - 5 : 0].y : 0u, bt[k + 1].x, bt[k + 1].y);
                        mma16816(a1, f[q - 4].z, f[q - 4].w, q > 4 ? f[q > 4 ? q - 5 : 0].w : 0u, bt[k + 1].z, bt[k + 1].w);
                    }
                }
                const uint32_t ya = yoff + O_Y12 + 136 * (4 + 2 * i) * 4;
                sts64f(ya, a0[0] + a1[0], a0[1] + a1[1]);
                sts64f(ya + 256, a0[2] + a1[2], a0[3] + a1[3]);
            }
        } else {
            const uint32_t wb = roff + ((lane >> 4) ? O_W4 : O_W3);
            uint4 bt[8];
#pragma unroll
            for (int k = 0; k < 8; k++) bt[k] = ldsm_x4_t(wb + (k - 1) * 256);
            const uint4 b5a = ldsm_x4_t(roff + O_W5 + (lane >> 4) * 512), b5b = ldsm_x4_t(roff + O_W5 + 1024 + (lane >> 4) * 512);
            const uint32_t kq = lds16(sb + O_KQ);
            const uint32_t dg = (g == 2 * tq) ? kq : ((g == 2 * tq + 1) ? (kq << 16) : 0u);
            float acc[4][4];
#pragma unroll
            for (int i = 0; i < 4; i++)
#pragma unroll
                for (int j = 0; j < 4; j++) acc[i][j] = 0.f;
            mma16816(acc[0], dg, 0u, 0u, b5a.x, b5a.y);
            mma16816(acc[1], dg, 0u, 0u, b5a.z, b5a.w);
            mma16816(acc[2], dg, 0u, 0u, b5b.x, b5b.y);
            mma16816(acc[3], dg, 0u, 0u, b5b.z, b5b.w);
            uint32_t pa = 0, pb = 0;
#pragma unroll
            for (int q = 8; q <= 15; q++) {
                const uint4 f = lds128(qoff + O_Q34 + (16 * q - 120) * 16);
#pragma unroll
                for (int i = 0; i < 4; i++) {
                    const int k = 2 * i + 8 - q;
                    if (k >= -1) mma16816(acc[i], f.x, f.y, pa, bt[k + 1].x, bt[k + 1].y);
                }
#pragma unroll
                for (int i = 0; i < 4; i++) {
                    const int k = 2 * i + 8 - q;
                    if (k >= -1) mma16816(acc[i], f.z, f.w, pb, bt[k + 1].z, bt[k + 1].w);
                }
                pa = f.y; pb = f.w;
            }
#pragma unroll
            for (int i = 0; i < 4; i++) {
                const uint32_t ya = yoff + O_Y34 + 136 * (8 + 2 * i) * 4;
                sts64f(ya, acc[i][0], acc[i][1]);
                sts64f(ya + 256, acc[i][2], acc[i][3]);
            }
        }
    }
    }
    wg_bar(bar);
    DBG1(7);
    {
        const uint32_t yb = sb + (136 * tq + 16 * w + g) * 4;
#pragma unroll
        for (int j = 1; j < 4; j++)
#pragma unroll
            for (int e = 0; e < 4; e++) {
                const uint32_t o = yb + (544 * j + 64 * (e & 1) + 8 * (e >> 1)) * 4;
                y[4 * j + e] += ldsf(o + O_Y12);
                if (j >= 2) y[4 * j + e] += ldsf(o + O_Y34);
            }
#pragma unroll
        for (int jp = 0; jp < 2; jp++) {
            const int a = 8 * (2 * jp + (lane >> 4)) + (lane & 7);
            const uint32_t addr = sb + O_ST + a * 128 + (((2 * w + ((lane >> 3) & 1)) ^ (lane & 7)) << 4);
            asm volatile("stmatrix.sync.aligned.m8n8.x4.trans.shared.b16 [%0], {%1,%2,%3,%4};" ::"r"(addr),
                         "r"(pack_bf16(y[8 * jp + 0], y[8 * jp + 1])), "r"(pack_bf16(y[8 * jp + 2], y[8 * jp + 3])),
                         "r"(pack_bf16(y[8 * jp + 4], y[8 * jp + 5])), "r"(pack_bf16(y[8 * jp + 6], y[8 * jp + 7]))
                         : "memory");
        }
        asm volatile("fence.proxy.async.shared::cta;" ::: "memory");
        wg_bar(bar);
        if (t == 0) {
            asm volatile("cp.async.bulk.tensor.2d.global.shared::cta.bulk_group [%0, {%1, %2}], [%3];"
                         ::"l"(tmo), "r"(0), "r"(d * 32), "r"(sb + O_ST) : "memory");
            asm volatile("cp.async.bulk.commit_group;" ::: "memory");
            asm volatile("cp.async.bulk.wait_group.read 0;" ::: "memory");
        }
        DBG1(8);
    }
}

constexpr int K1_WGS = 5;
constexpr int O_XTRA = K1_WGS * WG_BYTES;
constexpr int K1_SMEM = O_XTRA + 3 * 4096;
constexpr int K1_CTAS = (D_MODEL + K1_WGS - 1) / K1_WGS;
constexpr int K1_STAT = 16;
__device__ __forceinline__ uint32_t raw_box(uint32_t sbase, int i) {
    return i < K1_WGS ? sbase + i * WG_BYTES + O_RAW : sbase + O_XTRA + (i - K1_WGS) * 4096;
}
__device__ __forceinline__ void transpose_window(uint32_t sbase, int warp, int lane, int ch0) {
    const int ch = (lane >> 2) + ch0;
    const uint32_t ub = sbase + ch * WG_BYTES + (lane & 3) * 4;
#pragma unroll
    for (int k = 0; k < 4; k++) {
        const int gi = warp + k * (4 * K1_WGS);
        if (gi < 64) {
            const uint4 v = ldsm_x4_t(raw_box(sbase, gi >> 3) + (gi & 7) * 512 + lane * 16);
            if (ch >= 0 && ch < K1_WGS) {
                const uint32_t a0 = u_addr(ub, 4 * gi);
                sts32(a0, v.x);
                sts32(a0 ^ 16, v.y);
                sts32(a0 ^ 32, v.z);
                sts32(a0 ^ 48, v.w);
            }
        }
    }
}

__global__ void __launch_bounds__(128 * K1_WGS, 1)
ssm_kernel(const __grid_constant__ CUtensorMap tmc, const __grid_constant__ CUtensorMap tmo,
           const bf16* __restrict__ x, const bf16* __restrict__ gw, Params p) {
    extern __shared__ __align__(1024) uint8_t smem_raw[];
    const uint32_t sbase = smem_u32(smem_raw);
    const int tid = threadIdx.x, t = tid & 127, lane = tid & 31;
    const int wg = __shfl_sync(0xffffffffu, tid >> 7, 0), warp = __shfl_sync(0xffffffffu, tid >> 5, 0);
    const int d0 = blockIdx.x * K1_WGS, d = min(d0 + wg, D_MODEL - 1);
    const uint32_t sb = sbase + wg * WG_BYTES;
    const uint32_t xbar = sbase + WG_BYTES - 16;
    const int dw = d0 & ~7;
    const bool two = (d0 & 7) > 3 && dw + 8 < D_MODEL;
    DBG1(0);
    if (blockIdx.x == K1_CTAS) {
        if (tid == 0) {
            g_epoch = g_epoch + 1;
            asm volatile("fence.acq_rel.gpu;" ::: "memory");
        }
        __syncthreads();
    }
    asm volatile("griddepcontrol.launch_dependents;");
    if (blockIdx.x >= K1_CTAS) {
        const uint32_t tag = (g_stat_epoch[blockIdx.x - K1_CTAS] + 1) & 1u;
        __syncthreads();
        if (tid == 0) g_stat_epoch[blockIdx.x - K1_CTAS] = g_stat_epoch[blockIdx.x - K1_CTAS] + 1;
        uint32_t gr[9];
#pragma unroll
        for (int i = 0; i < 9; i++) gr[i] = __ldg(reinterpret_cast<const uint32_t*>(gw) + lane + 32 * i);
#pragma unroll 1
        for (int row = (blockIdx.x - K1_CTAS) * (4 * K1_WGS) + warp; row < L_SEQ; row += 2 * K1_STAT * 4 * K1_WGS) {
            const int row2 = min(row + K1_STAT * 4 * K1_WGS, L_SEQ - 1);
            uint32_t xr[2][9];
#pragma unroll
            for (int i = 0; i < 9; i++) {
                xr[0][i] = __ldg(reinterpret_cast<const uint32_t*>(x + (size_t)row * D_MODEL) + lane + 32 * i);
                xr[1][i] = __ldg(reinterpret_cast<const uint32_t*>(x + (size_t)row2 * D_MODEL) + lane + 32 * i);
            }
#pragma unroll
            for (int h = 0; h < 2; h++) {
                float s = 0.f, gs = 0.f;
#pragma unroll
                for (int i = 0; i < 9; i++) {
                    s += bf_lo(xr[h][i]) + bf_hi(xr[h][i]);
                    const uint32_t pr = hmul2_bf(xr[h][i], gr[i]);
                    gs += bf_lo(pr) + bf_hi(pr);
                }
#pragma unroll
                for (int o = 16; o; o >>= 1) {
                    s += __shfl_xor_sync(~0u, s, o);
                    gs += __shfl_xor_sync(~0u, gs, o);
                }
                const float mean = s * (1.f / D_MODEL);
                float q = 0.f;
#pragma unroll
                for (int i = 0; i < 9; i++) {
                    const float a = bf_lo(xr[h][i]) - mean, b = bf_hi(xr[h][i]) - mean;
                    q = fmaf(a, a, fmaf(b, b, q));
                }
#pragma unroll
                for (int o = 16; o; o >>= 1) q += __shfl_xor_sync(~0u, q, o);
                if (lane == 0) {
                    const float var = bf16r(q * (1.f / D_MODEL));
                    const float den = bf16r(sqrtf(bf16r(var + 1e-5f)));
                    const int r = h ? row2 : row;
                    const unsigned long long e = ((unsigned long long)((__float_as_uint(__fdividef(1.f, den)) & ~1u) | tag) << 32) |
                                                 pack_bf16(mean, mean);
                    asm volatile("st.relaxed.gpu.global.b64 [%0], %1;" ::"l"(&g_rowstat[r]), "l"(e) : "memory");
                    g_gate[r] = bf16r(__fdividef(1.f, 1.f + __expf(-bf16r(gs))));
                }
            }
        }
        return;
    }
    if (tid == 0) {
        mbar_init(xbar, 1);
        asm volatile("fence.mbarrier_init.release.cluster;" ::: "memory");
        mbar_expect(xbar, 8 * 4096);
#pragma unroll
        for (int i = 0; i < 8; i++) tma2d(raw_box(sbase, i), &tmc, dw, i * 256, xbar);
    }
    const ModeIn mi = load_mode(p, d, t);
    sts128(sb + O_U + t * 16, 0, 0, 0, 0);
    sts128(sb + O_KN + t * 16, 0, 0, 0, 0);
    gen_powers(mi, sb, t);
    DBG1(1);
    asm volatile("fence.proxy.async.shared::cta;" ::: "memory");
    __syncthreads();
    float kd[16];
    WG_FENCE();
    KgenSteps<16>::run(kd, (sb & 0x3FFFF) >> 4);
    WG_COMMIT();
    mbar_wait(xbar, 0);
    DBG1(2);
    transpose_window(sbase, warp, lane, dw - d0);
    if (two) {
        asm volatile("fence.proxy.async.shared::cta;" ::: "memory");
        __syncthreads();
        if (tid == 0) {
            mbar_expect(xbar, 8 * 4096);
#pragma unroll
            for (int i = 0; i < 8; i++) tma2d(raw_box(sbase, i), &tmc, dw + 8, i * 256, xbar);
        }
    }
    DBG1(3);
    WG_WAIT(0);
#pragma unroll
    for (int i = 0; i < 16; i++) asm volatile("" : "+f"(kd[i])::"memory");
    build_tables(kd, mi.dsk, sb, t, 1 + wg);
    if (two) {
        mbar_wait(xbar, 1);
        transpose_window(sbase, warp, lane, dw + 8 - d0);
    }
    asm volatile("fence.proxy.async.shared::cta;" ::: "memory");
    __syncthreads();
    DBG1(5);
    build_windows(sb, t);
    wg_bar(1 + wg);
    DBG1(9);
    if (d0 + wg < D_MODEL) convolve(d, sb, t, 1 + wg, &tmo);
}
}

constexpr int XT_BYTES = 128 * D_MODEL * 2;
constexpr int STAGE_BYTES = 96 * 128;
constexpr int NSTAGE = 6;
constexpr int SM_STAGES = XT_BYTES;
constexpr int SM_BARS = SM_STAGES + NSTAGE * STAGE_BYTES;
constexpr int SM_B1 = SM_BARS + 512;
constexpr int SM_B2 = SM_B1 + 576 * 4;
constexpr int MLP_SMEM = SM_B2 + 576 * 2;
__host__ __device__ constexpr int red_buf(int c) { return c < 7 ? c * 18432 : SM_STAGES + (c - 7) * 18432; }
constexpr int BAR_FULL = 0, BAR_EMPTY = 48, BAR_X = 96, BAR_PARKFREE = 168, BAR_STORED = 176, BAR_LOADED = 248, BAR_A = 320;

__device__ __forceinline__ float gelu2(float x) {
    const float k0 = 0.7978845608028654f, k1 = 0.7978845608028654f * 0.044715f;
    float u = x * fmaf(x * x, k1, k0);
    float th;
    asm("tanh.approx.f32 %0, %1;" : "=f"(th) : "f"(u));
    return fmaf(x, th, x);
}

__device__ __forceinline__ void epi_gelu(const float (&acc)[32], int i, uint32_t b1_addr, float r0, float r1,
                                         uint32_t (&o)[4]) {
    float b0, b1, b2, b3;
    asm volatile("ld.shared.v4.f32 {%0,%1,%2,%3}, [%4];"
                 : "=f"(b0), "=f"(b1), "=f"(b2), "=f"(b3) : "r"(b1_addr + i * 16));
    o[0] = pack_bf16(gelu2(fmaf(acc[8 * i + 0], r0, b0)), gelu2(fmaf(acc[8 * i + 1], r0, b1)));
    o[1] = pack_bf16(gelu2(fmaf(acc[8 * i + 2], r1, b0)), gelu2(fmaf(acc[8 * i + 3], r1, b1)));
    o[2] = pack_bf16(gelu2(fmaf(acc[8 * i + 4], r0, b2)), gelu2(fmaf(acc[8 * i + 5], r0, b3)));
    o[3] = pack_bf16(gelu2(fmaf(acc[8 * i + 6], r1, b2)), gelu2(fmaf(acc[8 * i + 7], r1, b3)));
}
__device__ __forceinline__ void epi_park(const float (&acc)[32], int i, uint32_t b1_addr, uint32_t park_addr,
                                         float r0, float r1) {
    uint32_t o[4];
    epi_gelu(acc, i, b1_addr, r0, r1, o);
    asm volatile("st.shared.v4.b32 [%0], {%1,%2,%3,%4};" ::"r"(park_addr + i * 4096), "r"(o[0]), "r"(o[1]),
                 "r"(o[2]), "r"(o[3]) : "memory");
}
__device__ __forceinline__ void epi_part(const float (&acc)[32], int i, uint4* part, uint32_t par) {
    uint4 v;
    v.x = (pack_bf16(acc[8 * i + 0], acc[8 * i + 1]) & ~1u) | par;
    v.y = pack_bf16(acc[8 * i + 2], acc[8 * i + 3]);
    v.z = (pack_bf16(acc[8 * i + 4], acc[8 * i + 5]) & ~1u) | par;
    v.w = pack_bf16(acc[8 * i + 6], acc[8 * i + 7]);
    asm volatile("{\n.reg .b128 q;\nmov.b128 q, {%1, %2};\nst.relaxed.gpu.global.b128 [%0], q;\n}\n" ::"l"(part + i * 32),
                 "l"(((unsigned long long)v.y << 32) | v.x), "l"(((unsigned long long)v.w << 32) | v.z) : "memory");
}
__device__ __forceinline__ void warp_arrive(uint32_t bar, int lane) {
    __syncwarp();
    if (lane == 0) asm volatile("mbarrier.arrive.shared::cta.b64 _, [%0];" ::"r"(bar) : "memory");
}

__device__ __forceinline__ void probe_partials(const uint4* unit, uint32_t par) {
    asm volatile(
        "{\n.reg .pred p;\n.reg .u32 n, v;\nmov.u32 n, 0;\n"
        "PROBE_LOOP:\n"
        "ld.relaxed.gpu.global.u32 v, [%0];\n"
        "xor.b32 v, v, %1;\n"
        "and.b32 v, v, 1;\n"
        "setp.ne.u32 p, v, 0;\n"
        "vote.sync.any.pred p, p, 0xffffffff;\n"
        "@!p bra PROBE_DONE;\n"
        "add.u32 n, n, 1;\n"
        "setp.lt.u32 p, n, 1048576;\n"
        "@p bra PROBE_LOOP;\n"
        "trap;\n"
        "PROBE_DONE:\n}\n" ::"l"(unit), "r"(par) : "memory");
}

__device__ __forceinline__ void finish_tile(int c, int tile, uint32_t sbase, uint32_t par, uint32_t gA, uint32_t gB,
                                            bf16* __restrict__ out) {
    const int lane = threadIdx.x & 31;
    const uint32_t buf = sbase + red_buf(c);
    const uint32_t a0 = buf + (tile >> 1) * 512 + lane * 16 + (tile & 1) * 8;
    uint2 v[8];
#pragma unroll
    for (int q = 0; q < 8; q++) v[q] = ssm::lds64(a0 + q * 2048);
    uint32_t ax, ay;
    asm volatile("ldmatrix.sync.aligned.m8n8.x2.trans.shared.b16 {%0,%1}, [%2];" : "=r"(ax), "=r"(ay)
                 : "r"(buf + 16384 + (lane & 7) * 32 + ((lane >> 3) & 1) * 16 + tile * 256) : "memory");
    const uint32_t bb = ssm::lds32(sbase + SM_B2 + c * 128 + (tile >> 1) * 32 + (lane & 3) * 8 + (tile & 1) * 4);
    const int m = blockIdx.x & 15, f = blockIdx.x >> 4;
    int tries = 0;
    while (true) {
        uint32_t bad = 0;
#pragma unroll
        for (int q = 0; q < 8; q++) bad |= v[q].x ^ par;
        if (!__any_sync(0xffffffffu, bad & 1)) break;
        const uint2* ps = reinterpret_cast<const uint2*>(
            g_part + ((m * 9 + c) * 8 + f) * (8 * 4 * 32) + (tile >> 1) * 32 + lane) + (tile & 1);
#pragma unroll
        for (int q = 0; q < 8; q++) {
            unsigned long long w;
            asm volatile("ld.relaxed.gpu.global.b64 %0, [%1];" : "=l"(w) : "l"(ps + q * 256) : "memory");
            v[q] = make_uint2((uint32_t)w, (uint32_t)(w >> 32));
        }
        if (++tries > (1 << 20)) break;
    }
    float sx0 = 0.f, sx1 = 0.f, sy0 = 0.f, sy1 = 0.f;
#pragma unroll
    for (int q = 0; q < 8; q++) {
        sx0 += bf_lo(v[q].x); sx1 += bf_hi(v[q].x);
        sy0 += bf_lo(v[q].y); sy1 += bf_hi(v[q].y);
    }
    const uint32_t half2 = 0x3f003f00u, one2 = 0x3f803f80u;
    uint32_t* o32 = reinterpret_cast<uint32_t*>(out + (m * 128 + f * 16 + (lane >> 2)) * D_MODEL + c * 64 + tile * 8 + 2 * (lane & 3));
    o32[0] = hadd2_bf(hmul2_bf(gA, ax), hmul2_bf(hsub2_bf(one2, gA), hfma2_bf(pack_bf16(sx0, sx1), half2, bb)));
    o32[4 * D_MODEL] = hadd2_bf(hmul2_bf(gB, ay), hmul2_bf(hsub2_bf(one2, gB), hfma2_bf(pack_bf16(sy0, sy1), half2, bb)));
}
constexpr int NFIN_HELP = 5;

template <int EPI>
__device__ __forceinline__ void run_chunk(float (&cur)[32], float (&prev)[32], const uint32_t (&af)[NAF][4],
                                          int parity, uint32_t bars, uint32_t desc0, uint32_t adesc0, uint32_t p0, uint32_t p1,
                                          uint4* part, bool sig, uint32_t rbar, int lane, float r0, float r1) {
#pragma unroll
    for (int s = 0; s < 6; s++) {
        mbar_wait(bars + BAR_FULL + s * 8, parity);
        WG_FENCE();
        mma_stage_rt(s, cur, af, desc0, adesc0);
        WG_COMMIT();
        if (s >= 1 && s <= 4) {
            if (EPI == 1) epi_park(prev, s - 1, p0, p1, r0, r1);
            if (EPI == 2) epi_part(prev, s - 1, part, p1);
        }
        if (s == 4 && EPI == 2) warp_arrive(p0, lane);
        WG_WAIT(1);
        if (sig) asm volatile("mbarrier.arrive.shared::cluster.b64 _, [%0];" ::"r"(rbar + ((s + 5) % 6) * 8) : "memory");
        if (s == 0) fence_acc(prev);
    }
}

__global__ void __cluster_dims__(2, 1, 1) __launch_bounds__(384, 1)
mlp_kernel(const __grid_constant__ CUtensorMap tmx, const __grid_constant__ CUtensorMap tmw1,
           const __grid_constant__ CUtensorMap tmw2, const __grid_constant__ CUtensorMap tma,
           const bf16* __restrict__ b1, const bf16* __restrict__ b2,
           bf16* __restrict__ out) {
    extern __shared__ __align__(1024) uint8_t smem_raw[];
    const uint32_t sbase = smem_u32(smem_raw);
    uint8_t* sgen = smem_raw;
    const int tid = threadIdx.x, lane = tid & 31;
    const int warp = __shfl_sync(0xffffffffu, tid >> 5, 0);
    const int wgid = __shfl_sync(0xffffffffu, tid >> 7, 0);
    const int m = blockIdx.x & 15, f = blockIdx.x >> 4;
    const uint32_t rank = m & 1;
    const uint32_t bars = sbase + SM_BARS;
    if (warp == 0) DBG(12);

    if (tid == 0) {
        if (sbase & 1023) asm volatile("trap; // 2");
        for (int i = 0; i < NSTAGE; i++) {
            mbar_init(bars + BAR_FULL + i * 8, 1);
            mbar_init(bars + BAR_EMPTY + i * 8, 4);
        }
        for (int i = 0; i < 9; i++) mbar_init(bars + BAR_X + i * 8, 1);
        mbar_init(bars + BAR_PARKFREE, 8);
        mbar_init(bars + BAR_A, 1);
        for (int i = 0; i < 9; i++) {
            mbar_init(bars + BAR_STORED + i * 8, 8);
            mbar_init(bars + BAR_LOADED + i * 8, 1);
        }
        asm volatile("fence.mbarrier_init.release.cluster;" ::: "memory");
        for (int j = 0; j < 3; j++) {
            mbar_expect(bars + BAR_X + j * 8, 16384);
            tma2d(sbase + j * 16384, &tmx, j * 64, m * 128, bars + BAR_X + j * 8);
        }
    }
    uint32_t b1v0 = 0, b1v1 = 0;
    if (wgid < 2) {
        const uint32_t* b1w = reinterpret_cast<const uint32_t*>(b1 + f * 576);
        b1v0 = __ldg(b1w + (tid >> 5) * 32 + (tid & 7) * 4 + ((tid >> 3) & 3));
        if (tid < 32) b1v1 = __ldg(b1w + 8 * 32 + (tid & 7) * 4 + ((tid >> 3) & 3));
    }
    __syncthreads();
    asm volatile("barrier.cluster.arrive.relaxed.aligned;\nbarrier.cluster.wait.aligned;" ::: "memory");

    if (warp == 0) DBG(0);
    if (wgid == 2) {
        asm volatile("setmaxnreg.dec.sync.aligned.u32 40;");
        if (warp == 8) {
            if (lane == 0) {
                const uint32_t dst0 = sbase + SM_STAGES + rank * (STAGE_BYTES / 2);
#pragma unroll 1
                for (int cc = 0; cc < 18; cc++) {
                    const CUtensorMap* tm = cc < 9 ? &tmw1 : &tmw2;
                    const int c0 = cc < 9 ? f * 576 + cc * 64 : (cc - 9) * 64;
                    const int c1 = (cc < 9 ? 0 : f * 576) + rank * 48;
                    const int par = (cc & 1) ^ 1;
#pragma unroll
                    for (int s = 0; s < 6; s++) {
                        mbar_wait(bars + BAR_EMPTY + s * 8, par);
                        mbar_expect(bars + BAR_FULL + s * 8, STAGE_BYTES);
                        tma2d_mc(dst0 + s * STAGE_BYTES, tm, c0, c1 + s * 96, bars + BAR_FULL + s * 8, 3);
                        if (cc == 0 && s >= 1 && s <= 3) {
#pragma unroll
                            for (int j = 2 * s + 1; j < 2 * s + 3; j++) {
                                mbar_expect(bars + BAR_X + j * 8, 16384);
                                tma2d(sbase + j * 16384, &tmx, j * 64, m * 128, bars + BAR_X + j * 8);
                            }
                        }
                    }
                }
            }
        } else if (warp == 9) {
            {
                uint32_t* b2s = reinterpret_cast<uint32_t*>(sgen + SM_B2);
                for (int w = lane; w < 288; w += 32) {
                    const int jj = w & 1, q = (w >> 1) & 3, ci = w >> 3;
                    b2s[w] = __ldg(reinterpret_cast<const uint32_t*>(b2) + ci * 8 + jj * 4 + q);
                }
                __syncwarp();
            }
            asm volatile("griddepcontrol.wait;" ::: "memory");
            const uint32_t par = __ldcg(&g_epoch);
            mbar_wait(bars + BAR_PARKFREE, 0);
            asm volatile("fence.proxy.async.shared::cta;" ::: "memory");
            const uint4* psrc = g_part + (m * 9 * 8 + f) * (8 * 4 * 32);
#pragma unroll 1
            for (int c = 0; c < 8; c++) {
                const uint32_t buf = sbase + red_buf(c);
                if (c == 7) {
                    mbar_wait(bars + BAR_EMPTY + 0, 1);
                    mbar_wait(bars + BAR_EMPTY + 8, 1);
                    mbar_wait(bars + BAR_EMPTY + 16, 1);
                }
                if (lane == 0) {
                    mbar_expect(bars + BAR_LOADED + c * 8, c < 8 ? 16384 + 2048 : 2048);
                    tma2d(buf + 16384, &tma, m * 128 + f * 16, c * 64, bars + BAR_LOADED + c * 8);
                    if (c == 7) {
                        mbar_expect(bars + BAR_LOADED + 64, 2048);
                        tma2d(sbase + red_buf(8) + 16384, &tma, m * 128 + f * 16, 8 * 64, bars + BAR_LOADED + 64);
                    }
                }
                mbar_wait(bars + BAR_STORED + c * 8, 0);
                probe_partials(psrc + (lane & 7) * 128 + 96 + 31, par);
                DBG(16 + c);
                if (lane == 0)
                    asm volatile("cp.async.bulk.shared::cluster.global.mbarrier::complete_tx::bytes [%0], [%1], 16384, [%2];"
                                 ::"r"(buf), "l"(psrc), "r"(bars + BAR_LOADED + c * 8) : "memory");
                psrc += 8 * 8 * 4 * 32;
            }
        }
        if (warp >= 10) {
            mbar_wait(bars + BAR_PARKFREE, 0);
            asm volatile("griddepcontrol.wait;" ::: "memory");
            const int t0 = m * 128 + f * 16 + (lane >> 2);
            const float g0 = __ldcg(&g_gate[t0]), g1 = __ldcg(&g_gate[t0 + 8]);
            const uint32_t par = __ldcg(&g_epoch) & 1u;
            const uint32_t gA = pack_bf16(g0, g0), gB = pack_bf16(g1, g1);
#pragma unroll 1
            for (int it = 0; it < NFIN_HELP * 4; it++) {
                if (!(it & 3)) mbar_wait(bars + BAR_LOADED + (it >> 2) * 8, 0);
                finish_tile(it >> 2, (it & 3) * 2 + (warp & 1), sbase, par, gA, gB, out);
            }
        }
        __syncwarp();
        asm volatile("barrier.cluster.arrive.relaxed.aligned;\nbarrier.cluster.wait.aligned;" ::: "memory");
    } else {
        asm volatile("setmaxnreg.inc.sync.aligned.u32 232;");
        const uint32_t par = __ldcg(&g_epoch) & 1u;
        uint2 rs0, rs1;
        {
            const uint2* rp = &g_rowstat[m * 128 + warp * 16 + (lane >> 2)];
            int tries = 0;
            while (true) {
                unsigned long long e0, e1;
                asm volatile("ld.relaxed.gpu.global.b64 %0, [%1];" : "=l"(e0) : "l"(rp) : "memory");
                asm volatile("ld.relaxed.gpu.global.b64 %0, [%1];" : "=l"(e1) : "l"(rp + 8) : "memory");
                rs0 = make_uint2((uint32_t)e0, (uint32_t)(e0 >> 32));
                rs1 = make_uint2((uint32_t)e1, (uint32_t)(e1 >> 32));
                if (!__any_sync(0xffffffffu, ((rs0.y ^ par) | (rs1.y ^ par)) & 1)) break;
                if (++tries > (1 << 22)) asm volatile("trap; // 3");
            }
        }
        const int g = lane >> 2, tq = lane & 3;
        uint32_t af[NAF][4];
        float acc0[32], acc1[32];
        const bool sig = (tid & 127) < 2;
        uint32_t rbar;
        asm volatile("mapa.shared::cluster.u32 %0, %1, %2;" : "=r"(rbar) : "r"(bars + BAR_EMPTY), "r"(tid & 1));
        const uint32_t desc0 = ((sbase + SM_STAGES) & 0x3FFFF) >> 4;
        const uint32_t adesc0 = ((sbase + 8 * 16384 + wgid * 8192) & 0x3FFFF) >> 4;

        {
            float2* b1s = reinterpret_cast<float2*>(sgen + SM_B1);
            b1s[tid] = make_float2(bf_lo(b1v0), bf_hi(b1v0));
            if (tid < 32) b1s[256 + tid] = make_float2(bf_lo(b1v1), bf_hi(b1v1));
        }
        const float rstd0 = __uint_as_float(rs0.y), rstd1 = __uint_as_float(rs1.y);
        {
            const int lrow = warp * 16 + (lane & 7) + ((lane >> 3) & 1) * 8;
            const uint32_t rbase = sbase + lrow * 128;
            const int hi = lane >> 4, sw = lrow & 7;
#pragma unroll
            for (int s = 0; s < 6; s++) {
#pragma unroll
                for (int k = s * 6; k < s * 6 + 6; k++) {
                    const int j = k >> 2, kk = k & 3;
                    if (kk == 0 || k == s * 6) mbar_wait(bars + BAR_X + j * 8, 0);
                    uint32_t tmp[4];
                    uint32_t (&a)[4] = (k < NAF) ? af[(k < NAF) ? k : 0] : tmp;
                    const uint32_t addr = rbase + j * 16384 + (((kk * 2 + hi) ^ sw) << 4);
                    ldsm_x4(a, addr);
                    a[0] = hsub2_bf(a[0], rs0.x);
                    a[1] = hsub2_bf(a[1], rs1.x);
                    a[2] = hsub2_bf(a[2], rs0.x);
                    a[3] = hsub2_bf(a[3], rs1.x);
                    if (k >= NAF) stsm_x4(a, addr);
                }
                if (s == 5) {
                    asm volatile("fence.proxy.async.shared::cta;" ::: "memory");
                    asm volatile("bar.sync %0, 128;" ::"r"(3 + wgid) : "memory");
                    if (warp == 0) DBG(1);
                }
                mbar_wait(bars + BAR_FULL + s * 8, 0);
                WG_FENCE();
                mma_stage_rt(s, acc0, af, desc0, adesc0);
                WG_COMMIT();
                if (s > 0) {
                    WG_WAIT(1);
                    if (sig) asm volatile("mbarrier.arrive.shared::cluster.b64 _, [%0];" ::"r"(rbar + (s - 1) * 8) : "memory");
                }
            }
            asm volatile("bar.sync 1, 256;" ::: "memory");
        }
        {
            uint32_t b1a = sbase + SM_B1 + tq * 64, park = sbase + tid * 16;
#pragma unroll 1
            for (int c = 1; c < 9; c += 2) {
                if (warp == 0) DBG(2 + (c >> 1));
                run_chunk<1>(acc1, acc0, af, 1, bars, desc0, adesc0, b1a, park, nullptr, sig, rbar, lane, rstd0, rstd1);
                run_chunk<1>(acc0, acc1, af, 0, bars, desc0, adesc0, b1a + 256, park + 16384, nullptr, sig, rbar, lane, rstd0, rstd1);
                b1a += 512;
                park += 32768;
            }
        }
        if (warp == 0) DBG(6);
        WG_WAIT(0);
        if (sig) asm volatile("mbarrier.arrive.shared::cluster.b64 _, [%0];" ::"r"(rbar + 5 * 8) : "memory");
        fence_acc(acc0);
#pragma unroll
        for (int k = 0; k < 32; k++)
            asm volatile("ld.shared.v4.b32 {%0,%1,%2,%3}, [%4];"
                         : "=r"(af[k][0]), "=r"(af[k][1]), "=r"(af[k][2]), "=r"(af[k][3])
                         : "r"(sbase + tid * 16 + k * 4096) : "memory");
        {
#pragma unroll
            for (int s = 0; s < 6; s++) {
                mbar_wait(bars + BAR_FULL + s * 8, 1);
                WG_FENCE();
                mma_stage_rt(s, acc1, af, desc0, adesc0);
                WG_COMMIT();
                if (s < 2) epi_gelu(acc0, s, sbase + SM_B1 + tq * 64 + 8 * 256, rstd0, rstd1, af[32 + (s & 1)]);
                if (s == 2 || s == 3) {
                    uint32_t tmp[4];
                    epi_gelu(acc0, s, sbase + SM_B1 + tq * 64 + 8 * 256, rstd0, rstd1, tmp);
                    const int lrow = warp * 16 + (lane & 7) + ((lane >> 3) & 1) * 8;
                    stsm_x4(tmp, sbase + 8 * 16384 + lrow * 128 + (((s * 2 + (lane >> 4)) ^ (lrow & 7)) << 4));
                }
                if (s == 3) {
                    asm volatile("fence.proxy.async.shared::cta;" ::: "memory");
                    asm volatile("bar.sync %0, 128;" ::"r"(3 + wgid) : "memory");
                }
                if (s > 0) {
                    WG_WAIT(1);
                    if (sig) asm volatile("mbarrier.arrive.shared::cluster.b64 _, [%0];" ::"r"(rbar + (s - 1) * 8) : "memory");
                }
                if (s == 5) warp_arrive(bars + BAR_PARKFREE, lane);
            }
        }
        uint4* part = g_part + (size_t)((m * 9 * 8 + warp) * 8 + f) * (4 * 32) + lane;
        uint32_t stored = bars + BAR_STORED;
#pragma unroll 1
        for (int c = 1; c < 9; c += 2) {
            if (warp == 0) DBG(7 + (c >> 1));
            run_chunk<2>(acc0, acc1, af, 0, bars, desc0, adesc0, stored, par, part, sig, rbar, lane, 0.f, 0.f);
            run_chunk<2>(acc1, acc0, af, 1, bars, desc0, adesc0, stored + 8, par, part + 8 * 8 * 4 * 32, sig, rbar, lane, 0.f, 0.f);
            part += 2 * 8 * 8 * 4 * 32;
            stored += 16;
        }
        const int t0 = m * 128 + f * 16 + g;
        asm volatile("griddepcontrol.wait;" ::: "memory");
        const float g0 = __ldcg(&g_gate[t0]), g1 = __ldcg(&g_gate[t0 + 8]);
        WG_WAIT(0);
        fence_acc(acc1);
#pragma unroll
        for (int i = 0; i < 4; i++) epi_part(acc1, i, part, par);
        asm volatile("barrier.cluster.arrive.relaxed.aligned;" ::: "memory");
        if (warp == 0) DBG(11);
        {
            const uint32_t gA = pack_bf16(g0, g0), gB = pack_bf16(g1, g1);
            const uint32_t half2 = 0x3f003f00u, one2 = 0x3f803f80u;
            const uint32_t oA = hsub2_bf(one2, gA), oB = hsub2_bf(one2, gB);
            uint32_t* o32 = reinterpret_cast<uint32_t*>(out + (size_t)t0 * D_MODEL + 2 * tq) + warp * 4;
            const uint32_t lm = sbase + 16384 + (lane & 7) * 32 + ((lane >> 3) & 1) * 16 + warp * 256;
            const uint32_t a0 = sbase + (warp >> 1) * 512 + lane * 16 + (warp & 1) * 8;
            const uint32_t b2a = sbase + SM_B2 + (warp >> 1) * 32 + tq * 8 + (warp & 1) * 4;
            const uint2* ps0 = reinterpret_cast<const uint2*>(
                g_part + (m * 9 * 8 + f) * (8 * 4 * 32) + (warp >> 1) * 32 + lane) + (warp & 1);
            uint2 v[4][8], av[4];
            uint32_t bb[4], bad = 0;
#pragma unroll
            for (int k = 0; k < 4; k++) {
                const int c = NFIN_HELP + k;
                const uint32_t bo = red_buf(c);
                mbar_wait(bars + BAR_LOADED + c * 8, 0);
                if (k < 3) {
#pragma unroll
                    for (int q = 0; q < 8; q++) {
                        v[k][q] = ssm::lds64(a0 + bo + q * 2048);
                        bad |= v[k][q].x ^ par;
                    }
                }
                asm volatile("ldmatrix.sync.aligned.m8n8.x2.trans.shared.b16 {%0,%1}, [%2];"
                             : "=r"(av[k].x), "=r"(av[k].y) : "r"(lm + bo) : "memory");
                bb[k] = ssm::lds32(b2a + c * 128);
            }
            auto emit = [&](int k) {
                const int c = NFIN_HELP + k;
                float sx0 = 0.f, sx1 = 0.f, sy0 = 0.f, sy1 = 0.f;
#pragma unroll
                for (int q = 0; q < 8; q++) {
                    sx0 += bf_lo(v[k][q].x); sx1 += bf_hi(v[k][q].x);
                    sy0 += bf_lo(v[k][q].y); sy1 += bf_hi(v[k][q].y);
                }
                o32[c * 32] = hadd2_bf(hmul2_bf(gA, av[k].x), hmul2_bf(oA, hfma2_bf(pack_bf16(sx0, sx1), half2, bb[k])));
                o32[c * 32 + 4 * D_MODEL] =
                    hadd2_bf(hmul2_bf(gB, av[k].y), hmul2_bf(oB, hfma2_bf(pack_bf16(sy0, sy1), half2, bb[k])));
            };
            auto reload = [&](int k) {
                uint32_t b = 0;
#pragma unroll
                for (int q = 0; q < 8; q++) {
                    unsigned long long w;
                    asm volatile("ld.relaxed.gpu.global.b64 %0, [%1];" : "=l"(w)
                                 : "l"(ps0 + (NFIN_HELP + k) * (8 * 8 * 4 * 32 * 2) + q * 256) : "memory");
                    v[k][q] = make_uint2((uint32_t)w, (uint32_t)(w >> 32));
                    b |= v[k][q].x ^ par;
                }
                return b;
            };
            int tries = 0;
            while (__any_sync(0xffffffffu, bad & 1)) {
                bad = reload(0) | reload(1) | reload(2);
                if (++tries > (1 << 20)) break;
            }
            emit(0); emit(1); emit(2);
            if (warp == 0) DBG(32);
            probe_partials(g_part + ((m * 9 + 8) * 8 + f) * (8 * 4 * 32) + (lane & 7) * 128 + (warp >> 1) * 32 + 31, par);
            do {
                bad = reload(3);
                if (++tries > (1 << 20)) break;
            } while (__any_sync(0xffffffffu, bad & 1));
            emit(3);
            if (warp == 0) DBG(33);
        }
        asm volatile("barrier.cluster.wait.aligned;" ::: "memory");
        if (warp == 0) DBG(13);
    }
}

typedef CUresult (*EncodeFn)(CUtensorMap*, CUtensorMapDataType, cuuint32_t, void*, const cuuint64_t*,
                             const cuuint64_t*, const cuuint32_t*, const cuuint32_t*, CUtensorMapInterleave,
                             CUtensorMapSwizzle, CUtensorMapL2promotion, CUtensorMapFloatOOBfill);

static void make_map(EncodeFn enc, CUtensorMap* m, const void* ptr, uint64_t cols, uint64_t rows, uint32_t box_c,
                     uint32_t box_r, CUtensorMapSwizzle swz = CU_TENSOR_MAP_SWIZZLE_128B) {
    cuuint64_t dim[2] = {cols, rows};
    cuuint64_t str[1] = {cols * 2};
    cuuint32_t box[2] = {box_c, box_r};
    cuuint32_t es[2] = {1, 1};
    enc(m, CU_TENSOR_MAP_DATA_TYPE_BFLOAT16, 2, const_cast<void*>(ptr), dim, str, box, es,
        CU_TENSOR_MAP_INTERLEAVE_NONE, swz, CU_TENSOR_MAP_L2_PROMOTION_L2_128B,
        CU_TENSOR_MAP_FLOAT_OOB_FILL_NONE);
}

}

extern "C" void kernel_launch(void* const* d_in, const int* in_sizes, int n_in, void* d_out, int out_size) {
    const bf16* u = (const bf16*)d_in[0];
    const bf16* A_re = (const bf16*)d_in[1];
    const bf16* A_im = (const bf16*)d_in[2];
    const bf16* B_re = (const bf16*)d_in[3];
    const bf16* B_im = (const bf16*)d_in[4];
    const bf16* C_re = (const bf16*)d_in[5];
    const bf16* C_im = (const bf16*)d_in[6];
    const bf16* log_dt = (const bf16*)d_in[7];
    const bf16* Dskip = (const bf16*)d_in[8];
    const bf16* w1 = (const bf16*)d_in[10];
    const bf16* b1 = (const bf16*)d_in[11];
    const bf16* w2 = (const bf16*)d_in[12];
    const bf16* b2 = (const bf16*)d_in[13];
    const bf16* gw = (const bf16*)d_in[14];
    bf16* out = (bf16*)d_out;

    static EncodeFn enc = nullptr;
    if (!enc) {
        void* fn = nullptr;
        cudaDriverEntryPointQueryResult q;
        cudaGetDriverEntryPoint("cuTensorMapEncodeTiled", &fn, cudaEnableDefault, &q);
        enc = (EncodeFn)fn;
        cudaFuncSetAttribute(mlp_kernel, cudaFuncAttributeMaxDynamicSharedMemorySize, MLP_SMEM);
        cudaFuncSetAttribute(ssm::ssm_kernel, cudaFuncAttributeMaxDynamicSharedMemorySize, ssm::K1_SMEM);
    }
    static void* aT_ptr = nullptr;
    if (!aT_ptr) cudaGetSymbolAddress(&aT_ptr, g_aT);
    CUtensorMap tmx, tmw1, tmw2, tma;
    make_map(enc, &tma, aT_ptr, L_SEQ, D_MODEL, 16, 64, CU_TENSOR_MAP_SWIZZLE_NONE);
    make_map(enc, &tmx, u, D_MODEL, L_SEQ, 64, 128);
    make_map(enc, &tmw1, w1, F_DIM, D_MODEL, 64, 48);
    make_map(enc, &tmw2, w2, D_MODEL, F_DIM, 64, 48);

    cudaStream_t st = cudaStreamPerThread;
    ssm::Params sp{A_re, A_im, B_re, B_im, C_re, C_im, log_dt, Dskip};
    CUtensorMap tmc, tmo;
    make_map(enc, &tmc, u, D_MODEL, L_SEQ, 8, 256, CU_TENSOR_MAP_SWIZZLE_NONE);
    make_map(enc, &tmo, aT_ptr, 64, D_MODEL * 32, 64, 32);
    ssm::ssm_kernel<<<ssm::K1_CTAS + ssm::K1_STAT, 128 * ssm::K1_WGS, ssm::K1_SMEM, st>>>(tmc, tmo, u, gw, sp);
    cudaLaunchConfig_t cfg = {};
    cfg.gridDim = dim3(128);
    cfg.blockDim = dim3(384);
    cfg.dynamicSmemBytes = MLP_SMEM;
    cfg.stream = st;
    cudaLaunchAttribute at[1];
    at[0].id = cudaLaunchAttributeProgrammaticStreamSerialization;
    at[0].val.programmaticStreamSerializationAllowed = 1;
    cfg.attrs = at;
    cfg.numAttrs = 1;
    cudaLaunchKernelEx(&cfg, mlp_kernel, tmx, tmw1, tmw2, tma, b1, b2, out);
}
```

```cpp
#include <cuda_runtime.h>
#include <cuda_bf16.h>
#include <cuda.h>
#include <stdint.h>

namespace {

constexpr int L_SEQ = 2048;
constexpr int D_MODEL = 576;
constexpr int F_DIM = 4608;
constexpr int N_MODES = 128;

typedef __nv_bfloat16 bf16;

__device__ uint2 g_rowstat[L_SEQ];
__device__ float g_gate[L_SEQ];
__device__ bf16 g_aT[D_MODEL * L_SEQ];
__device__ uint4 g_part[16 * 9 * 8 * 8 * 4 * 32];
__device__ unsigned g_stat_epoch[16];
__device__ unsigned g_epoch;

#define DBG(slot)
#define DBG1(slot)

__device__ __forceinline__ uint32_t smem_u32(const void* p) { return (uint32_t)__cvta_generic_to_shared(p); }
__device__ __forceinline__ float bf16r(float x) { return __bfloat162float(__float2bfloat16_rn(x)); }
__device__ __forceinline__ uint32_t pack_bf16(float lo, float hi) {
    uint32_t r;
    asm("cvt.rn.bf16x2.f32 %0, %1, %2;" : "=r"(r) : "f"(hi), "f"(lo));
    return r;
}
__device__ __forceinline__ float bf_lo(uint32_t v) { return __uint_as_float(v << 16); }
__device__ __forceinline__ float bf_hi(uint32_t v) { return __uint_as_float(v & 0xffff0000u); }

__device__ __forceinline__ void mbar_init(uint32_t bar, int cnt) {
    asm volatile("mbarrier.init.shared::cta.b64 [%0], %1;" ::"r"(bar), "r"(cnt));
}
__device__ __forceinline__ void mbar_expect(uint32_t bar, int bytes) {
    asm volatile("mbarrier.arrive.expect_tx.shared::cta.b64 _, [%0], %1;" ::"r"(bar), "r"(bytes) : "memory");
}
__device__ __forceinline__ void mbar_wait(uint32_t bar, int parity) {
    asm volatile(
        "{\n.reg .pred p;\n.reg .u32 n;\nmov.u32 n, 0;\n"
        "WAIT_LOOP:\n"
        "mbarrier.try_wait.parity.shared::cta.b64 p, [%0], %1;\n"
        "@p bra WAIT_DONE;\n"
        "add.u32 n, n, 1;\n"
        "setp.lt.u32 p, n, 4194304;\n"
        "@p bra WAIT_LOOP;\n"
        "trap;\n"
        "WAIT_DONE:\n}\n" ::"r"(bar), "r"(parity) : "memory");
}
__device__ __forceinline__ void tma2d(uint32_t dst, const CUtensorMap* m, int c0, int c1, uint32_t bar) {
    asm volatile(
        "cp.async.bulk.tensor.2d.shared::cluster.global.mbarrier::complete_tx::bytes [%0], [%1, {%3,%4}], [%2];"
        ::"r"(dst), "l"(m), "r"(bar), "r"(c0), "r"(c1) : "memory");
}
__device__ __forceinline__ void tma2d_mc(uint32_t dst, const CUtensorMap* m, int c0, int c1, uint32_t bar,
                                         uint16_t mask) {
    asm volatile(
        "cp.async.bulk.tensor.2d.shared::cluster.global.mbarrier::complete_tx::bytes.multicast::cluster "
        "[%0], [%1, {%3,%4}], [%2], %5;"
        ::"r"(dst), "l"(m), "r"(bar), "r"(c0), "r"(c1), "h"(mask) : "memory");
}
__device__ __forceinline__ void ldsm_x4(uint32_t (&r)[4], uint32_t addr) {
    asm volatile("ldmatrix.sync.aligned.m8n8.x4.shared.b16 {%0,%1,%2,%3}, [%4];"
                 : "=r"(r[0]), "=r"(r[1]), "=r"(r[2]), "=r"(r[3]) : "r"(addr) : "memory");
}
#define WG_FENCE() asm volatile("wgmma.fence.sync.aligned;\n" ::: "memory")
#define WG_COMMIT() asm volatile("wgmma.commit_group.sync.aligned;\n" ::: "memory")
#define WG_WAIT(n) asm volatile("wgmma.wait_group.sync.aligned %0;\n" ::"n"(n) : "memory")

template <int SCALE_D, int OFF>
__device__ __forceinline__ void wgmma_rs_n64(float (&d)[32], const uint32_t (&a)[4], uint32_t desc_lo) {
    asm volatile(
        "{\n.reg .pred p;\n.reg .b32 lo;\n.reg .b64 dsc;\nsetp.ne.b32 p, %37, 0;\n"
        "add.u32 lo, %36, %38;\nmov.b64 dsc, {lo, 0x40000040};\n"
        "wgmma.mma_async.sync.aligned.m64n64k16.f32.bf16.bf16 "
        "{%0,%1,%2,%3,%4,%5,%6,%7,%8,%9,%10,%11,%12,%13,%14,%15,%16,%17,%18,%19,%20,%21,%22,%23,%24,%25,%26,%27,%28,%29,%30,%31},"
        "{%32,%33,%34,%35}, dsc, p, 1, 1, 1;\n}\n"
        : "+f"(d[0]), "+f"(d[1]), "+f"(d[2]), "+f"(d[3]), "+f"(d[4]), "+f"(d[5]), "+f"(d[6]), "+f"(d[7]),
          "+f"(d[8]), "+f"(d[9]), "+f"(d[10]), "+f"(d[11]), "+f"(d[12]), "+f"(d[13]), "+f"(d[14]), "+f"(d[15]),
          "+f"(d[16]), "+f"(d[17]), "+f"(d[18]), "+f"(d[19]), "+f"(d[20]), "+f"(d[21]), "+f"(d[22]), "+f"(d[23]),
          "+f"(d[24]), "+f"(d[25]), "+f"(d[26]), "+f"(d[27]), "+f"(d[28]), "+f"(d[29]), "+f"(d[30]), "+f"(d[31])
        : "r"(a[0]), "r"(a[1]), "r"(a[2]), "r"(a[3]), "r"(desc_lo), "n"(SCALE_D), "n"(OFF));
}
template <int OFF, int AOFF>
__device__ __forceinline__ void wgmma_ss_n64(float (&d)[32], uint32_t adesc_lo, uint32_t desc_lo) {
    asm volatile(
        "{\n.reg .pred p;\n.reg .b32 lo;\n.reg .b64 dsc, dsa;\nsetp.ne.b32 p, 1, 0;\n"
        "add.u32 lo, %33, %34;\nmov.b64 dsc, {lo, 0x40000040};\n"
        "add.u32 lo, %32, %35;\nmov.b64 dsa, {lo, 0x40000040};\n"
        "wgmma.mma_async.sync.aligned.m64n64k16.f32.bf16.bf16 "
        "{%0,%1,%2,%3,%4,%5,%6,%7,%8,%9,%10,%11,%12,%13,%14,%15,%16,%17,%18,%19,%20,%21,%22,%23,%24,%25,%26,%27,%28,%29,%30,%31},"
        "dsa, dsc, p, 1, 1, 0, 1;\n}\n"
        : "+f"(d[0]), "+f"(d[1]), "+f"(d[2]), "+f"(d[3]), "+f"(d[4]), "+f"(d[5]), "+f"(d[6]), "+f"(d[7]),
          "+f"(d[8]), "+f"(d[9]), "+f"(d[10]), "+f"(d[11]), "+f"(d[12]), "+f"(d[13]), "+f"(d[14]), "+f"(d[15]),
          "+f"(d[16]), "+f"(d[17]), "+f"(d[18]), "+f"(d[19]), "+f"(d[20]), "+f"(d[21]), "+f"(d[22]), "+f"(d[23]),
          "+f"(d[24]), "+f"(d[25]), "+f"(d[26]), "+f"(d[27]), "+f"(d[28]), "+f"(d[29]), "+f"(d[30]), "+f"(d[31])
        : "r"(adesc_lo), "r"(desc_lo), "n"(OFF), "n"(AOFF));
}
constexpr int NAF = 34;
template <int S, int FIRST>
__device__ __forceinline__ void mma_stage(float (&d)[32], const uint32_t (&af)[NAF][4], uint32_t desc_lo,
                                          uint32_t adesc_lo) {
    constexpr int B = (S * 96 * 128) >> 4;
    wgmma_rs_n64<FIRST ? 0 : 1, B + 0 * 128>(d, af[S * 6 + 0], desc_lo);
    wgmma_rs_n64<1, B + 1 * 128>(d, af[S * 6 + 1], desc_lo);
    wgmma_rs_n64<1, B + 2 * 128>(d, af[S * 6 + 2], desc_lo);
    wgmma_rs_n64<1, B + 3 * 128>(d, af[S * 6 + 3], desc_lo);
    if constexpr (S < 5) {
        wgmma_rs_n64<1, B + 4 * 128>(d, af[S * 6 + 4], desc_lo);
        wgmma_rs_n64<1, B + 5 * 128>(d, af[S * 6 + 5], desc_lo);
    } else {
        wgmma_ss_n64<B + 4 * 128, 4>(d, adesc_lo, desc_lo);
        wgmma_ss_n64<B + 5 * 128, 6>(d, adesc_lo, desc_lo);
    }
}
__device__ __forceinline__ void mma_stage_rt(int s, float (&d)[32], const uint32_t (&af)[NAF][4], uint32_t desc_lo,
                                             uint32_t adesc_lo) {
    if (s == 0) mma_stage<0, 1>(d, af, desc_lo, adesc_lo);
    if (s == 1) mma_stage<1, 0>(d, af, desc_lo, adesc_lo);
    if (s == 2) mma_stage<2, 0>(d, af, desc_lo, adesc_lo);
    if (s == 3) mma_stage<3, 0>(d, af, desc_lo, adesc_lo);
    if (s == 4) mma_stage<4, 0>(d, af, desc_lo, adesc_lo);
    if (s == 5) mma_stage<5, 0>(d, af, desc_lo, adesc_lo);
}
__device__ __forceinline__ void stsm_x4(const uint32_t (&r)[4], uint32_t addr) {
    asm volatile("stmatrix.sync.aligned.m8n8.x4.shared.b16 [%4], {%0,%1,%2,%3};"
                 ::"r"(r[0]), "r"(r[1]), "r"(r[2]), "r"(r[3]), "r"(addr) : "memory");
}
__device__ __forceinline__ void fence_acc(float (&d)[32]) {
#pragma unroll
    for (int i = 0; i < 32; i++) asm volatile("" : "+f"(d[i])::"memory");
}

__device__ __forceinline__ uint32_t hadd2_bf(uint32_t a, uint32_t b) {
    uint32_t r;
    asm("add.rn.bf16x2 %0, %1, %2;" : "=r"(r) : "r"(a), "r"(b));
    return r;
}
__device__ __forceinline__ uint32_t hsub2_bf(uint32_t a, uint32_t b) {
    uint32_t r;
    asm("sub.rn.bf16x2 %0, %1, %2;" : "=r"(r) : "r"(a), "r"(b));
    return r;
}
__device__ __forceinline__ uint32_t hmul2_bf(uint32_t a, uint32_t b) {
    uint32_t r;
    asm("mul.rn.bf16x2 %0, %1, %2;" : "=r"(r) : "r"(a), "r"(b));
    return r;
}
__device__ __forceinline__ uint32_t hfma2_bf(uint32_t a, uint32_t b, uint32_t c) {
    uint32_t r;
    asm("fma.rn.bf16x2 %0, %1, %2, %3;" : "=r"(r) : "r"(a), "r"(b), "r"(c));
    return r;
}
namespace ssm {
constexpr int O_H = 0;
constexpr int O_L = 12288;
constexpr int HL_END = O_L + 16384;
constexpr int O_Q = 0;
constexpr int O_Q12 = 5120;
constexpr int O_Q34 = O_Q12 + 1280;
constexpr int O_Y12 = O_Q34 + 2048 - 2176;
constexpr int O_Y34 = O_Y12 + 8704 - 4352;
constexpr int O_W3 = O_Y34 + 8704 + 256;
constexpr int O_W4 = O_W3 + 2048 + 256;
constexpr int O_W5 = O_W4 + 2048;
constexpr int O_U = HL_END;
constexpr int O_RAW = O_U + 6144;
constexpr int O_W1 = O_U + 6144 + 256;
constexpr int O_W2 = O_W1 + 3072 + 256;
constexpr int O_ST = O_RAW;
constexpr int O_KN = O_W2 + 3072;
constexpr int O_A12 = O_KN + 1344;
constexpr int O_A3 = O_A12 + 384;
constexpr int O_KQ = O_A3 + 304;
constexpr int WG_BYTES = 44032;
static_assert(O_W5 + 2048 <= HL_END && O_KQ + 16 <= WG_BYTES && WG_BYTES % 1024 == 0 && O_RAW + 8192 <= WG_BYTES, "map");

struct cplx { float r, i; };
__device__ __forceinline__ cplx cmul(cplx a, cplx b) {
    cplx o;
    o.r = fmaf(a.r, b.r, -a.i * b.i);
    o.i = fmaf(a.r, b.i, a.i * b.r);
    return o;
}
__device__ __forceinline__ cplx cexp_l(float lr, float li, float l) {
    const float e = exp2f((lr * l) * 1.4426950408889634f);
    const float ang = li * l;
    const float k = rintf(ang * 0.15915494309189535f);
    float r = fmaf(k, -6.2831854820251465f, ang);
    r = fmaf(k, 1.7484556000744487e-07f, r);
    cplx o;
    o.r = e * __cosf(r);
    o.i = e * __sinf(r);
    return o;
}
template <typename T> __device__ __forceinline__ T* sp(uint32_t a) {
    return reinterpret_cast<T*>(__cvta_shared_to_generic(a));
}
__device__ __forceinline__ void sts32(uint32_t a, uint32_t v) { *sp<uint32_t>(a) = v; }
__device__ __forceinline__ void sts16(uint32_t a, uint32_t v) { *sp<unsigned short>(a) = (unsigned short)v; }
__device__ __forceinline__ uint32_t lds16(uint32_t a) { return *sp<unsigned short>(a); }
__device__ __forceinline__ uint32_t lds32(uint32_t a) { return *sp<uint32_t>(a); }
__device__ __forceinline__ float ldsf(uint32_t a) { return *sp<float>(a); }
__device__ __forceinline__ uint2 lds64(uint32_t a) { return *sp<uint2>(a); }
__device__ __forceinline__ void sts64(uint32_t a, uint32_t x, uint32_t y) { *sp<uint2>(a) = make_uint2(x, y); }
__device__ __forceinline__ void sts64f(uint32_t a, float x, float y) { *sp<float2>(a) = make_float2(x, y); }
__device__ __forceinline__ void sts128(uint32_t a, uint32_t x, uint32_t y, uint32_t z, uint32_t w) {
    *sp<uint4>(a) = make_uint4(x, y, z, w);
}
__device__ __forceinline__ uint4 lds128(uint32_t a) { return *sp<uint4>(a); }
__device__ __forceinline__ void wg_bar(int id) { asm volatile("bar.sync %0, 128;" ::"r"(id) : "memory"); }
__device__ __forceinline__ uint32_t u_addr(uint32_t sb, int grp) {
    const int gq = grp + 128;
    return sb + O_U + (gq >> 3) * 128 + (((gq ^ (gq >> 3)) & 7) << 4);
}
template <int SCALE_D, int OA, int OB>
__device__ __forceinline__ void wgmma_ss_n32(float (&d)[16], uint32_t dl) {
    asm volatile(
        "{\n.reg .pred p;\n.reg .b32 lo;\n.reg .b64 x, y;\nsetp.ne.b32 p, %17, 0;\n"
        "add.u32 lo, %16, %18;\nmov.b64 x, {lo, 0x40000040};\nadd.u32 lo, %16, %19;\nmov.b64 y, {lo, 0x40000040};\n"
        "wgmma.mma_async.sync.aligned.m64n32k16.f32.bf16.bf16 "
        "{%0,%1,%2,%3,%4,%5,%6,%7,%8,%9,%10,%11,%12,%13,%14,%15}, x, y, p, 1, 1, 0, 0;\n}\n"
        : "+f"(d[0]), "+f"(d[1]), "+f"(d[2]), "+f"(d[3]), "+f"(d[4]), "+f"(d[5]), "+f"(d[6]), "+f"(d[7]),
          "+f"(d[8]), "+f"(d[9]), "+f"(d[10]), "+f"(d[11]), "+f"(d[12]), "+f"(d[13]), "+f"(d[14]), "+f"(d[15])
        : "r"(dl), "n"(SCALE_D), "n"(OA), "n"(OB));
}
template <int OB>
__device__ __forceinline__ void wgmma_rs_n32(float (&d)[16], uint32_t a0, uint32_t a1, uint32_t a2, uint32_t a3,
                                             uint32_t dl) {
    asm volatile(
        "{\n.reg .pred p;\n.reg .b32 lo;\n.reg .b64 y;\nsetp.ne.b32 p, 1, 0;\n"
        "add.u32 lo, %20, %21;\nmov.b64 y, {lo, 0x40000040};\n"
        "wgmma.mma_async.sync.aligned.m64n32k16.f32.bf16.bf16 "
        "{%0,%1,%2,%3,%4,%5,%6,%7,%8,%9,%10,%11,%12,%13,%14,%15}, {%16,%17,%18,%19}, y, p, 1, 1, 0;\n}\n"
        : "+f"(d[0]), "+f"(d[1]), "+f"(d[2]), "+f"(d[3]), "+f"(d[4]), "+f"(d[5]), "+f"(d[6]), "+f"(d[7]),
          "+f"(d[8]), "+f"(d[9]), "+f"(d[10]), "+f"(d[11]), "+f"(d[12]), "+f"(d[13]), "+f"(d[14]), "+f"(d[15])
        : "r"(a0), "r"(a1), "r"(a2), "r"(a3), "r"(dl), "n"(OB));
}
template <int KS> struct KgenSteps {
    static __device__ __forceinline__ void run(float (&d)[16], uint32_t dl) {
        KgenSteps<KS - 1>::run(d, dl);
        constexpr int k = KS - 1;
        wgmma_ss_n32<(k > 0), (O_H + (k / 4) * 3072 + (k % 4) * 32) / 16, (O_L + (k / 4) * 4096 + (k % 4) * 32) / 16>(d, dl);
    }
};
template <> struct KgenSteps<0> { static __device__ __forceinline__ void run(float (&)[16], uint32_t) {} };
template <int K0, int N, int I> struct NearSteps {
    static __device__ __forceinline__ void run(float (&d)[16], const uint4 (&f)[N], uint32_t dl) {
        NearSteps<K0, N, I - 1>::run(d, f, dl);
        constexpr int k = K0 + I - 1, dd = k / 4, kk = 4 * dd - (k - 3);
        wgmma_rs_n32<(O_U + (16 - dd) * 128 + kk * 32) / 16>(d, f[I - 1].x, f[I - 1].y, f[I - 1].z, f[I - 1].w, dl);
    }
};
template <int K0, int N> struct NearSteps<K0, N, 0> {
    static __device__ __forceinline__ void run(float (&)[16], const uint4 (&)[N], uint32_t) {}
};
template <int N>
__device__ __forceinline__ void load_toep(uint4 (&f)[N], uint32_t addr, uint32_t& prev) {
#pragma unroll
    for (int k = 0; k < N; k++)
    { const uint2 v = lds64(addr + k * 128); f[k].x = v.x; f[k].y = v.y; }
#pragma unroll
    for (int k = 0; k < N; k++) {
        f[k].z = prev;
        f[k].w = f[k].x;
        prev = f[k].y;
    }
}
__device__ __forceinline__ void mma16816(float (&d)[4], uint32_t a0, uint32_t a1, uint32_t a2, uint32_t b0,
                                         uint32_t b1) {
    asm("mma.sync.aligned.m16n8k16.row.col.f32.bf16.bf16.f32 {%0,%1,%2,%3}, {%4,%5,%6,%4}, {%7,%8}, {%0,%1,%2,%3};"
                 : "+f"(d[0]), "+f"(d[1]), "+f"(d[2]), "+f"(d[3])
                 : "r"(a0), "r"(a1), "r"(a2), "r"(b0), "r"(b1));
}
__device__ __forceinline__ uint4 ldsm_x4_t(uint32_t addr) {
    uint4 r;
    asm volatile("ldmatrix.sync.aligned.m8n8.x4.trans.shared.b16 {%0,%1,%2,%3}, [%4];"
                 : "=r"(r.x), "=r"(r.y), "=r"(r.z), "=r"(r.w) : "r"(addr));
    return r;
}
struct Params { const bf16 *A_re, *A_im, *B_re, *B_im, *C_re, *C_im, *log_dt, *Dskip; };
struct ModeIn { float ar, ai, br, bi, cr, ci, ldt, dsk; };
__device__ __forceinline__ ModeIn load_mode(const Params& p, int d, int n) {
    ModeIn m;
    const int i = d * N_MODES + n;
    m.ar = __bfloat162float(p.A_re[i]); m.ai = __bfloat162float(p.A_im[i]);
    m.br = __bfloat162float(p.B_re[i]); m.bi = __bfloat162float(p.B_im[i]);
    m.cr = __bfloat162float(p.C_re[i]); m.ci = __bfloat162float(p.C_im[i]);
    m.ldt = __bfloat162float(p.log_dt[d]); m.dsk = __bfloat162float(p.Dskip[d]);
    return m;
}

__device__ __forceinline__ void gen_powers(const ModeIn& mi, uint32_t sb, int t) {
    const float dt = bf16r(expf(mi.ldt));
    const float lr = dt * mi.ar, li = dt * mi.ai;
    const float br = dt * mi.br, bi = dt * mi.bi;
    cplx c;
    c.r = mi.cr * br - mi.ci * bi;
    c.i = mi.cr * bi + mi.ci * br;
    const cplx z = cexp_l(lr, li, 1.f), wv = cexp_l(lr, li, 8.f), Z = cexp_l(lr, li, 256.f);
    const cplx z2 = cmul(z, z), z4 = cmul(z2, z2);
    const uint32_t x0 = ((t & 31) >> 2) * 16 + (t & 3) * 4;
    uint32_t xs[8];
#pragma unroll
    for (int j = 0; j < 8; j++) xs[j] = sb + (x0 ^ (j << 4));
    const uint32_t ho = O_H + (t >> 5) * 3072, lo_ = O_L + (t >> 5) * 4096;
#define PUT_H(row, v) sts32(xs[(row) & 7] + ho + (row) * 128, pack_bf16((v).r, -(v).i))
#define PUT_L(row, v) sts32(xs[(row) & 7] + lo_ + (row) * 128, pack_bf16((v).r, (v).i))
    cplx h = c;
    PUT_H(0, h);
#pragma unroll
    for (int k = 1; k < 8; k++) { h = cmul(h, z); PUT_H(k, h); }
    cplx hz = cmul(c, Z);
    PUT_H(8, hz);
    { cplx a = cmul(hz, z2); PUT_H(9, a); a = cmul(hz, z4); PUT_H(10, a); a = cmul(a, z2); PUT_H(11, a); }
    hz = cmul(hz, Z); PUT_H(12, hz);
    { cplx a = cmul(hz, z4); PUT_H(13, a); }
    hz = cmul(hz, Z); PUT_H(14, hz);
    { cplx a = cmul(hz, z4); PUT_H(15, a); }
#pragma unroll
    for (int k = 16; k < 21; k++) { hz = cmul(hz, Z); PUT_H(k, hz); }
    const cplx w2 = cmul(wv, wv);
    cplx le, lo = wv;
    le.r = 1.f; le.i = 0.f;
    uint32_t lb = lo_;
#pragma unroll 1
    for (int kb = 0; kb < 4; kb++) {
#pragma unroll
        for (int k = 0; k < 8; k += 2) {
            sts32(xs[k] + lb + k * 128, pack_bf16(le.r, le.i));
            sts32(xs[k + 1] + lb + (k + 1) * 128, pack_bf16(lo.r, lo.i));
            le = cmul(le, w2); lo = cmul(lo, w2);
        }
        lb += 1024;
    }
}

__device__ __forceinline__ uint4 pack8(const float (&v)[8]) {
    return make_uint4(pack_bf16(v[0], v[1]), pack_bf16(v[2], v[3]), pack_bf16(v[4], v[5]), pack_bf16(v[6], v[7]));
}
__device__ __forceinline__ void st16B(uint32_t a, const uint4& v) { *sp<uint4>(a) = v; }

__device__ __forceinline__ void build_windows(uint32_t sb, int t) {
    if (t < 64) {
        const int which = t >> 4;
        sts128(sb + (which == 0 ? O_W1 : which == 1 ? O_W2 : which == 2 ? O_W3 : O_W4) - 256 + (t & 15) * 16, 0, 0, 0, 0);
    }
#pragma unroll
    for (int r = 0; r < 2; r++) {
        const int grp = t + r * 128;
        if (grp < 192) {
            const uint4 c0 = lds128(u_addr(sb, grp - 2)), c1 = lds128(u_addr(sb, grp - 1)), c2 = lds128(u_addr(sb, grp));
            float v[24];
            const uint32_t ww[12] = {c0.x, c0.y, c0.z, c0.w, c1.x, c1.y, c1.z, c1.w, c2.x, c2.y, c2.z, c2.w};
#pragma unroll
            for (int i = 2; i < 11; i++) { v[2 * i] = bf_lo(ww[i]); v[2 * i + 1] = bf_hi(ww[i]); }
            float p2[15];
#pragma unroll
            for (int j = 0; j < 15; j++) p2[j] = v[5 + j] + v[6 + j];
            float b1[8], b2[8];
#pragma unroll
            for (int i = 0; i < 8; i++) {
                b2[i] = p2[i + 6] + v[13 + i];
                b1[i] = p2[i + 1] + p2[i + 3] + v[10 + i];
            }
            st16B(sb + O_W1 + grp * 16, pack8(b1));
            st16B(sb + O_W2 + grp * 16, pack8(b2));
            if (r == 0) {
                float b3[8], b5[8];
#pragma unroll
                for (int i = 0; i < 8; i++) {
                    b3[i] = b1[i] + v[11 + i] + v[5 + i];
                    b5[i] = p2[i + 7];
                }
                st16B(sb + O_W3 + grp * 16, pack8(b3));
                st16B(sb + O_W5 + grp * 16, pack8(b5));
                st16B(sb + O_W4 + grp * 16, make_uint4(hadd2_bf(ww[6], ww[2]), hadd2_bf(ww[7], ww[3]),
                                                       hadd2_bf(ww[8], ww[4]), hadd2_bf(ww[9], ww[5])));
            }
        }
    }
}

__device__ __forceinline__ void build_tables(float (&kd)[16], float dskip, uint32_t sb, int t, int bar) {
    const int lane = t & 31, w = t >> 5, g = lane >> 2, tq = lane & 3;
    if (w == 0) {
        if (lane == 0) kd[0] += dskip;
        const uint32_t kn = sb + O_KN + 128;
#pragma unroll
        for (int j = 0; j < 4; j++) {
            const int lo = 8 * j + 2 * tq;
            const uint32_t p0 = pack_bf16(kd[4 * j], kd[4 * j + 1]), p1 = pack_bf16(kd[4 * j + 2], kd[4 * j + 3]);
            sts16(kn + (g + 8 * lo) * 2, p0);
            sts16(kn + (g + 8 * lo + 8) * 2, p0 >> 16);
            if (g < 4) {
#pragma unroll
                for (int e = 0; e < 2; e++) {
                    const uint32_t val = e ? (p1 >> 16) : p1, ad = kn + (256 + 2 * g + 8 * (lo + e)) * 2;
                    sts16(ad, val);
                    if (!(g & 1)) {
                        sts16(ad + 2, val);
                        if (g + lo + e > 0) sts16(ad - 2, val);
                    }
                }
            } else {
#pragma unroll
                for (int e = 0; e < 2; e++) {
                    const uint32_t val = e ? (p1 >> 16) : p1;
                    const int i8 = 64 + (g >= 6 ? 32 : 0) + lo + e;
                    if (j > 0 || i8 >= 66) {
                        sts16(sb + O_A12 + (i8 - 48) * 4 - ((g & 1) ? 0 : 2), val);
                    } else if (g & 1) {
                        sts16(kn + (8 * i8 + 3) * 2, val); sts16(kn + (8 * i8 + 4) * 2, val); sts16(kn + (8 * i8 + 5) * 2, val);
                    } else {
#pragma unroll
                        for (int dd = -2; dd <= 2; dd++)
                            if (i8 == 65 || dd >= -1) sts16(kn + (8 * i8 + dd) * 2, val);
                    }
                }
            }
        }
    } else if (w == 1) {
        if (g < 4) {
#pragma unroll
            for (int j = 0; j < 4; j++) {
                const int i8 = 128 + 32 * g + 8 * j + 2 * tq;
                const uint32_t p0 = pack_bf16(kd[4 * j], kd[4 * j + 1]);
                if (i8 == 128) { sts16(sb + O_A12 + (127 - 48) * 4 + 2, p0); sts16(sb + O_KQ, p0); }
                else sts16(sb + O_A3 + (i8 - 1 - 112) * 2, p0);
                sts16(sb + O_A3 + (i8 - 112) * 2, p0 >> 16);
            }
        } else if (lane == 16) {
            sts16(sb + O_A3 + (255 - 112) * 2, pack_bf16(kd[0], 0.f));
        }
    }
    wg_bar(bar);
    DBG1(4);
    {
#pragma unroll
        for (int r = 0; r < 2; r++) {
            const int i = t + r * 128;
            if (i < 160) {
                const uint32_t ka = sb + O_KN + (4 * i + 8) * 2;
                const uint32_t wm = lds32(ka - 4), w3 = lds32(ka + 12);
                const uint2 wa = lds64(ka), wb = lds64(ka + 16);
                const uint32_t w0 = wa.x, w1 = wa.y, w4 = wb.x, w5 = wb.y;
                sts128(sb + O_Q + i * 32, __byte_perm(w0, wm, 0x7610), __byte_perm(w4, w3, 0x7610),
                       __byte_perm(w0, w0, 0x1032), __byte_perm(w4, w4, 0x1032));
                sts128(sb + O_Q + i * 32 + 16, __byte_perm(w1, w0, 0x7610), __byte_perm(w5, w4, 0x7610),
                       __byte_perm(w1, w1, 0x1032), __byte_perm(w5, w5, 0x1032));
            }
        }
        {
            const uint32_t aa = sb + O_A3 + (8 + t) * 2;
            const uint32_t p0 = lds16(aa) | (lds16(aa - 2) << 16), p1 = lds16(aa + 16) | (lds16(aa + 14) << 16);
            const uint32_t msk = (t & 1) ? 0x0000ffffu : 0xffff0000u;
            sts128(sb + O_Q34 + t * 16, p0, p1, p0 & msk, p1 & msk);
        }
        if (t >= 48) {
            const uint32_t aa = sb + O_A12 + (t - 48 + 8) * 4;
            const uint32_t e0 = lds32(aa), e1 = lds32(aa - 4), f0 = lds32(aa + 32), f1 = lds32(aa + 28);
            sts128(sb + O_Q12 + (t - 48) * 16, __byte_perm(e0, e1, 0x7632), __byte_perm(f0, f1, 0x7632),
                   __byte_perm(e0, e1, 0x5410), __byte_perm(f0, f1, 0x5410));
        }
    }
}

__device__ __forceinline__ void convolve(int d, uint32_t sb, int t, int bar, const CUtensorMap* tmo) {
    const int lane = t & 31, w = t >> 5, g = lane >> 2, tq = lane & 3;
    const uint32_t dl = (sb & 0x3FFFF) >> 4;
    float y[16];
#pragma unroll
    for (int i = 0; i < 16; i++) y[i] = 0.f;
#pragma unroll 1
    for (int step = 0; step < 2; step++) {
    if ((step ^ bar) & 1) {
        const uint32_t qa = sb + O_Q + (16 * w + g - 2 * tq + 56 - 48) * 8;
        uint32_t prev = 0;
        uint32_t qp = qa, du = dl;
#pragma unroll 1
        for (int jj = 0; jj < 4; jj++) {
            uint4 F[8];
            load_toep<8>(F, qp, prev);
            WG_FENCE();
            NearSteps<0, 8, 8>::run(y, F, du);
            WG_COMMIT();
            WG_WAIT(0);
            qp += 8 * 128;
            du -= 16;
        }
        uint4 FC[5];
        load_toep<5>(FC, qp, prev);
        WG_FENCE();
        NearSteps<0, 5, 5>::run(y, FC, du);
        WG_COMMIT();
        WG_WAIT(0);
#pragma unroll
        for (int i = 0; i < 16; i++) asm volatile("" : "+f"(y[i])::"memory");
    } else {
        const int par = w & 1;
        const uint32_t qoff = sb + (g - 2 * tq) * 16;
        const uint32_t roff = sb + (lane & 15) * 16 + par * 256;
        const uint32_t yoff = sb + (136 * par + 8 * g + 2 * tq) * 4;
        if (w < 2) {
            const uint32_t wb = roff + ((lane >> 4) ? O_W2 : O_W1);
            uint4 f[5];
#pragma unroll
            for (int q = 4; q <= 8; q++) f[q - 4] = lds128(qoff + O_Q12 + (16 * q - 56) * 16);
            uint4 bt[12];
#pragma unroll
            for (int i = 0; i < 6; i++) {
                if (i == 0) bt[0] = ldsm_x4_t(wb - 256);
                bt[2 * i + 1] = ldsm_x4_t(wb + (2 * i) * 256);
                if (i > 0) bt[2 * i] = ldsm_x4_t(wb + (2 * i - 1) * 256);
                float a0[4] = {0.f, 0.f, 0.f, 0.f}, a1[4] = {0.f, 0.f, 0.f, 0.f};
#pragma unroll
                for (int q = 4; q <= 8; q++) {
                    const int k = 2 * i + 4 - q;
                    if (k >= -1) {
                        mma16816(a0, f[q - 4].x, f[q - 4].y, q > 4 ? f[q > 4 ? q - 5 : 0].y : 0u, bt[k + 1].x, bt[k + 1].y);
                        mma16816(a1, f[q - 4].z, f[q - 4].w, q > 4 ? f[q > 4 ? q - 5 : 0].w : 0u, bt[k + 1].z, bt[k + 1].w);
                    }
                }
                const uint32_t ya = yoff + O_Y12 + 136 * (4 + 2 * i) * 4;
                sts64f(ya, a0[0] + a1[0], a0[1] + a1[1]);
                sts64f(ya + 256, a0[2] + a1[2], a0[3] + a1[3]);
            }
        } else {
            const uint32_t wb = roff + ((lane >> 4) ? O_W4 : O_W3);
            uint4 bt[8];
#pragma unroll
            for (int k = 0; k < 8; k++) bt[k] = ldsm_x4_t(wb + (k - 1) * 256);
            const uint4 b5a = ldsm_x4_t(roff + O_W5 + (lane >> 4) * 512), b5b = ldsm_x4_t(roff + O_W5 + 1024 + (lane >> 4) * 512);
            const uint32_t kq = lds16(sb + O_KQ);
            const uint32_t dg = (g == 2 * tq) ? kq : ((g == 2 * tq + 1) ? (kq << 16) : 0u);
            float acc[4][4];
#pragma unroll
            for (int i = 0; i < 4; i++)
#pragma unroll
                for (int j = 0; j < 4; j++) acc[i][j] = 0.f;
            mma16816(acc[0], dg, 0u, 0u, b5a.x, b5a.y);
            mma16816(acc[1], dg, 0u, 0u, b5a.z, b5a.w);
            mma16816(acc[2], dg, 0u, 0u, b5b.x, b5b.y);
            mma16816(acc[3], dg, 0u, 0u, b5b.z, b5b.w);
            uint32_t pa = 0, pb = 0;
#pragma unroll
            for (int q = 8; q <= 15; q++) {
                const uint4 f = lds128(qoff + O_Q34 + (16 * q - 120) * 16);
#pragma unroll
                for (int i = 0; i < 4; i++) {
                    const int k = 2 * i + 8 - q;
                    if (k >= -1) mma16816(acc[i], f.x, f.y, pa, bt[k + 1].x, bt[k + 1].y);
                }
#pragma unroll
                for (int i = 0; i < 4; i++) {
                    const int k = 2 * i + 8 - q;
                    if (k >= -1) mma16816(acc[i], f.z, f.w, pb, bt[k + 1].z, bt[k + 1].w);
                }
                pa = f.y; pb = f.w;
            }
#pragma unroll
            for (int i = 0; i < 4; i++) {
                const uint32_t ya = yoff + O_Y34 + 136 * (8 + 2 * i) * 4;
                sts64f(ya, acc[i][0], acc[i][1]);
                sts64f(ya + 256, acc[i][2], acc[i][3]);
            }
        }
    }
    }
    wg_bar(bar);
    DBG1(7);
    {
        const uint32_t yb = sb + (136 * tq + 16 * w + g) * 4;
#pragma unroll
        for (int j = 1; j < 4; j++)
#pragma unroll
            for (int e = 0; e < 4; e++) {
                const uint32_t o = yb + (544 * j + 64 * (e & 1) + 8 * (e >> 1)) * 4;
                y[4 * j + e] += ldsf(o + O_Y12);
                if (j >= 2) y[4 * j + e] += ldsf(o + O_Y34);
            }
#pragma unroll
        for (int jp = 0; jp < 2; jp++) {
            const int a = 8 * (2 * jp + (lane >> 4)) + (lane & 7);
            const uint32_t addr = sb + O_ST + a * 128 + (((2 * w + ((lane >> 3) & 1)) ^ (lane & 7)) << 4);
            asm volatile("stmatrix.sync.aligned.m8n8.x4.trans.shared.b16 [%0], {%1,%2,%3,%4};" ::"r"(addr),
                         "r"(pack_bf16(y[8 * jp + 0], y[8 * jp + 1])), "r"(pack_bf16(y[8 * jp + 2], y[8 * jp + 3])),
                         "r"(pack_bf16(y[8 * jp + 4], y[8 * jp + 5])), "r"(pack_bf16(y[8 * jp + 6], y[8 * jp + 7]))
                         : "memory");
        }
        asm volatile("fence.proxy.async.shared::cta;" ::: "memory");
        wg_bar(bar);
        if (t == 0) {
            asm volatile("cp.async.bulk.tensor.2d.global.shared::cta.bulk_group [%0, {%1, %2}], [%3];"
                         ::"l"(tmo), "r"(0), "r"(d * 32), "r"(sb + O_ST) : "memory");
            asm volatile("cp.async.bulk.commit_group;" ::: "memory");
            asm volatile("cp.async.bulk.wait_group.read 0;" ::: "memory");
        }
        DBG1(8);
    }
}

constexpr int K1_WGS = 5;
constexpr int O_XTRA = K1_WGS * WG_BYTES;
constexpr int K1_SMEM = O_XTRA + 3 * 4096;
constexpr int K1_CTAS = (D_MODEL + K1_WGS - 1) / K1_WGS;
constexpr int K1_STAT = 16;
__device__ __forceinline__ uint32_t raw_box(uint32_t sbase, int i) {
    return i < K1_WGS ? sbase + i * WG_BYTES + O_RAW : sbase + O_XTRA + (i - K1_WGS) * 4096;
}
__device__ __forceinline__ void transpose_window(uint32_t sbase, int warp, int lane, int ch0) {
    const int ch = (lane >> 2) + ch0;
    const uint32_t ub = sbase + ch * WG_BYTES + (lane & 3) * 4;
#pragma unroll
    for (int k = 0; k < 4; k++) {
        const int gi = warp + k * (4 * K1_WGS);
        if (gi < 64) {
            const uint4 v = ldsm_x4_t(raw_box(sbase, gi >> 3) + (gi & 7) * 512 + lane * 16);
            if (ch >= 0 && ch < K1_WGS) {
                const uint32_t a0 = u_addr(ub, 4 * gi);
                sts32(a0, v.x);
                sts32(a0 ^ 16, v.y);
                sts32(a0 ^ 32, v.z);
                sts32(a0 ^ 48, v.w);
            }
        }
    }
}

__global__ void __launch_bounds__(128 * K1_WGS, 1)
ssm_kernel(const __grid_constant__ CUtensorMap tmc, const __grid_constant__ CUtensorMap tmo,
           const bf16* __restrict__ x, const bf16* __restrict__ gw, Params p) {
    extern __shared__ __align__(1024) uint8_t smem_raw[];
    const uint32_t sbase = smem_u32(smem_raw);
    const int tid = threadIdx.x, t = tid & 127, lane = tid & 31;
    const int wg = __shfl_sync(0xffffffffu, tid >> 7, 0), warp = __shfl_sync(0xffffffffu, tid >> 5, 0);
    const int d0 = blockIdx.x * K1_WGS, d = min(d0 + wg, D_MODEL - 1);
    const uint32_t sb = sbase + wg * WG_BYTES;
    const uint32_t xbar = sbase + WG_BYTES - 16;
    const int dw = d0 & ~7;
    const bool two = (d0 & 7) > 3 && dw + 8 < D_MODEL;
    DBG1(0);
    if (blockIdx.x == K1_CTAS) {
        if (tid == 0) {
            g_epoch = g_epoch + 1;
            asm volatile("fence.acq_rel.gpu;" ::: "memory");
        }
        __syncthreads();
    }
    asm volatile("griddepcontrol.launch_dependents;");
    if (blockIdx.x >= K1_CTAS) {
        const uint32_t tag = (g_stat_epoch[blockIdx.x - K1_CTAS] + 1) & 1u;
        __syncthreads();
        if (tid == 0) g_stat_epoch[blockIdx.x - K1_CTAS] = g_stat_epoch[blockIdx.x - K1_CTAS] + 1;
        uint32_t gr[9];
#pragma unroll
        for (int i = 0; i < 9; i++) gr[i] = __ldg(reinterpret_cast<const uint32_t*>(gw) + lane + 32 * i);
#pragma unroll 1
        for (int row = (blockIdx.x - K1_CTAS) * (4 * K1_WGS) + warp; row < L_SEQ; row += 2 * K1_STAT * 4 * K1_WGS) {
            const int row2 = min(row + K1_STAT * 4 * K1_WGS, L_SEQ - 1);
            uint32_t xr[2][9];
#pragma unroll
            for (int i = 0; i < 9; i++) {
                xr[0][i] = __ldg(reinterpret_cast<const uint32_t*>(x + (size_t)row * D_MODEL) + lane + 32 * i);
                xr[1][i] = __ldg(reinterpret_cast<const uint32_t*>(x + (size_t)row2 * D_MODEL) + lane + 32 * i);
            }
#pragma unroll
            for (int h = 0; h < 2; h++) {
                float s = 0.f, gs = 0.f;
#pragma unroll
                for (int i = 0; i < 9; i++) {
                    s += bf_lo(xr[h][i]) + bf_hi(xr[h][i]);
                    const uint32_t pr = hmul2_bf(xr[h][i], gr[i]);
                    gs += bf_lo(pr) + bf_hi(pr);
                }
#pragma unroll
                for (int o = 16; o; o >>= 1) {
                    s += __shfl_xor_sync(~0u, s, o);
                    gs += __shfl_xor_sync(~0u, gs, o);
                }
                const float mean = s * (1.f / D_MODEL);
                float q = 0.f;
#pragma unroll
                for (int i = 0; i < 9; i++) {
                    const float a = bf_lo(xr[h][i]) - mean, b = bf_hi(xr[h][i]) - mean;
                    q = fmaf(a, a, fmaf(b, b, q));
                }
#pragma unroll
                for (int o = 16; o; o >>= 1) q += __shfl_xor_sync(~0u, q, o);
                if (lane == 0) {
                    const float var = bf16r(q * (1.f / D_MODEL));
                    const float den = bf16r(sqrtf(bf16r(var + 1e-5f)));
                    const int r = h ? row2 : row;
                    const unsigned long long e = ((unsigned long long)((__float_as_uint(__fdividef(1.f, den)) & ~1u) | tag) << 32) |
                                                 pack_bf16(mean, mean);
                    asm volatile("st.relaxed.gpu.global.b64 [%0], %1;" ::"l"(&g_rowstat[r]), "l"(e) : "memory");
                    g_gate[r] = bf16r(__fdividef(1.f, 1.f + __expf(-bf16r(gs))));
                }
            }
        }
        return;
    }
    if (tid == 0) {
        mbar_init(xbar, 1);
        asm volatile("fence.mbarrier_init.release.cluster;" ::: "memory");
        mbar_expect(xbar, 8 * 4096);
#pragma unroll
        for (int i = 0; i < 8; i++) tma2d(raw_box(sbase, i), &tmc, dw, i * 256, xbar);
    }
    const ModeIn mi = load_mode(p, d, t);
    sts128(sb + O_U + t * 16, 0, 0, 0, 0);
    sts128(sb + O_KN + t * 16, 0, 0, 0, 0);
    gen_powers(mi, sb, t);
    DBG1(1);
    asm volatile("fence.proxy.async.shared::cta;" ::: "memory");
    __syncthreads();
    float kd[16];
    WG_FENCE();
    KgenSteps<16>::run(kd, (sb & 0x3FFFF) >> 4);
    WG_COMMIT();
    mbar_wait(xbar, 0);
    DBG1(2);
    transpose_window(sbase, warp, lane, dw - d0);
    if (two) {
        asm volatile("fence.proxy.async.shared::cta;" ::: "memory");
        __syncthreads();
        if (tid == 0) {
            mbar_expect(xbar, 8 * 4096);
#pragma unroll
            for (int i = 0; i < 8; i++) tma2d(raw_box(sbase, i), &tmc, dw + 8, i * 256, xbar);
        }
    }
    DBG1(3);
    WG_WAIT(0);
#pragma unroll
    for (int i = 0; i < 16; i++) asm volatile("" : "+f"(kd[i])::"memory");
    build_tables(kd, mi.dsk, sb, t, 1 + wg);
    if (two) {
        mbar_wait(xbar, 1);
        transpose_window(sbase, warp, lane, dw + 8 - d0);
    }
    asm volatile("fence.proxy.async.shared::cta;" ::: "memory");
    __syncthreads();
    DBG1(5);
    build_windows(sb, t);
    wg_bar(1 + wg);
    DBG1(9);
    if (d0 + wg < D_MODEL) convolve(d, sb, t, 1 + wg, &tmo);
}
}

constexpr int XT_BYTES = 128 * D_MODEL * 2;
constexpr int STAGE_BYTES = 96 * 128;
constexpr int NSTAGE = 6;
constexpr int SM_STAGES = XT_BYTES;
constexpr int SM_BARS = SM_STAGES + NSTAGE * STAGE_BYTES;
constexpr int SM_B1 = SM_BARS + 512;
constexpr int SM_B2 = SM_B1 + 576 * 4;
constexpr int MLP_SMEM = SM_B2 + 576 * 2;
__host__ __device__ constexpr int red_buf(int c) { return c < 7 ? c * 18432 : SM_STAGES + (c - 7) * 18432; }
constexpr int BAR_FULL = 0, BAR_EMPTY = 48, BAR_X = 96, BAR_PARKFREE = 168, BAR_STORED = 176, BAR_LOADED = 248, BAR_A = 320;

__device__ __forceinline__ float gelu2(float x) {
    const float k0 = 0.7978845608028654f, k1 = 0.7978845608028654f * 0.044715f;
    float u = x * fmaf(x * x, k1, k0);
    float th;
    asm("tanh.approx.f32 %0, %1;" : "=f"(th) : "f"(u));
    return fmaf(x, th, x);
}

__device__ __forceinline__ void epi_gelu(const float (&acc)[32], int i, uint32_t b1_addr, float r0, float r1,
                                         uint32_t (&o)[4]) {
    float b0, b1, b2, b3;
    asm volatile("ld.shared.v4.f32 {%0,%1,%2,%3}, [%4];"
                 : "=f"(b0), "=f"(b1), "=f"(b2), "=f"(b3) : "r"(b1_addr + i * 16));
    o[0] = pack_bf16(gelu2(fmaf(acc[8 * i + 0], r0, b0)), gelu2(fmaf(acc[8 * i + 1], r0, b1)));
    o[1] = pack_bf16(gelu2(fmaf(acc[8 * i + 2], r1, b0)), gelu2(fmaf(acc[8 * i + 3], r1, b1)));
    o[2] = pack_bf16(gelu2(fmaf(acc[8 * i + 4], r0, b2)), gelu2(fmaf(acc[8 * i + 5], r0, b3)));
    o[3] = pack_bf16(gelu2(fmaf(acc[8 * i + 6], r1, b2)), gelu2(fmaf(acc[8 * i + 7], r1, b3)));
}
__device__ __forceinline__ void epi_park(const float (&acc)[32], int i, uint32_t b1_addr, uint32_t park_addr,
                                         float r0, float r1) {
    uint32_t o[4];
    epi_gelu(acc, i, b1_addr, r0, r1, o);
    asm volatile("st.shared.v4.b32 [%0], {%1,%2,%3,%4};" ::"r"(park_addr + i * 4096), "r"(o[0]), "r"(o[1]),
                 "r"(o[2]), "r"(o[3]) : "memory");
}
__device__ __forceinline__ void epi_part(const float (&acc)[32], int i, uint4* part, uint32_t par) {
    uint4 v;
    v.x = (pack_bf16(acc[8 * i + 0], acc[8 * i + 1]) & ~1u) | par;
    v.y = pack_bf16(acc[8 * i + 2], acc[8 * i + 3]);
    v.z = (pack_bf16(acc[8 * i + 4], acc[8 * i + 5]) & ~1u) | par;
    v.w = pack_bf16(acc[8 * i + 6], acc[8 * i + 7]);
    asm volatile("{\n.reg .b128 q;\nmov.b128 q, {%1, %2};\nst.relaxed.gpu.global.b128 [%0], q;\n}\n" ::"l"(part + i * 32),
                 "l"(((unsigned long long)v.y << 32) | v.x), "l"(((unsigned long long)v.w << 32) | v.z) : "memory");
}
__device__ __forceinline__ void warp_arrive(uint32_t bar, int lane) {
    __syncwarp();
    if (lane == 0) asm volatile("mbarrier.arrive.shared::cta.b64 _, [%0];" ::"r"(bar) : "memory");
}

__device__ __forceinline__ void probe_partials(const uint4* unit, uint32_t par) {
    asm volatile(
        "{\n.reg .pred p;\n.reg .u32 n, v;\nmov.u32 n, 0;\n"
        "PROBE_LOOP:\n"
        "ld.relaxed.gpu.global.u32 v, [%0];\n"
        "xor.b32 v, v, %1;\n"
        "and.b32 v, v, 1;\n"
        "setp.ne.u32 p, v, 0;\n"
        "vote.sync.any.pred p, p, 0xffffffff;\n"
        "@!p bra PROBE_DONE;\n"
        "add.u32 n, n, 1;\n"
        "setp.lt.u32 p, n, 1048576;\n"
        "@p bra PROBE_LOOP;\n"
        "trap;\n"
        "PROBE_DONE:\n}\n" ::"l"(unit), "r"(par) : "memory");
}

__device__ __forceinline__ void finish_tile(int c, int tile, uint32_t sbase, uint32_t par, uint32_t gA, uint32_t gB,
                                            bf16* __restrict__ out) {
    const int lane = threadIdx.x & 31;
    const uint32_t buf = sbase + red_buf(c);
    const uint32_t a0 = buf + (tile >> 1) * 512 + lane * 16 + (tile & 1) * 8;
    uint2 v[8];
#pragma unroll
    for (int q = 0; q < 8; q++) v[q] = ssm::lds64(a0 + q * 2048);
    uint32_t ax, ay;
    asm volatile("ldmatrix.sync.aligned.m8n8.x2.trans.shared.b16 {%0,%1}, [%2];" : "=r"(ax), "=r"(ay)
                 : "r"(buf + 16384 + (lane & 7) * 32 + ((lane >> 3) & 1) * 16 + tile * 256) : "memory");
    const uint32_t bb = ssm::lds32(sbase + SM_B2 + c * 128 + (tile >> 1) * 32 + (lane & 3) * 8 + (tile & 1) * 4);
    const int m = blockIdx.x & 15, f = blockIdx.x >> 4;
    int tries = 0;
    while (true) {
        uint32_t bad = 0;
#pragma unroll
        for (int q = 0; q < 8; q++) bad |= v[q].x ^ par;
        if (!__any_sync(0xffffffffu, bad & 1)) break;
        const uint2* ps = reinterpret_cast<const uint2*>(
            g_part + ((m * 9 + c) * 8 + f) * (8 * 4 * 32) + (tile >> 1) * 32 + lane) + (tile & 1);
#pragma unroll
        for (int q = 0; q < 8; q++) {
            unsigned long long w;
            asm volatile("ld.relaxed.gpu.global.b64 %0, [%1];" : "=l"(w) : "l"(ps + q * 256) : "memory");
            v[q] = make_uint2((uint32_t)w, (uint32_t)(w >> 32));
        }
        if (++tries > (1 << 20)) break;
    }
    float sx0 = 0.f, sx1 = 0.f, sy0 = 0.f, sy1 = 0.f;
#pragma unroll
    for (int q = 0; q < 8; q++) {
        sx0 += bf_lo(v[q].x); sx1 += bf_hi(v[q].x);
        sy0 += bf_lo(v[q].y); sy1 += bf_hi(v[q].y);
    }
    const uint32_t half2 = 0x3f003f00u, one2 = 0x3f803f80u;
    uint32_t* o32 = reinterpret_cast<uint32_t*>(out + (m * 128 + f * 16 + (lane >> 2)) * D_MODEL + c * 64 + tile * 8 + 2 * (lane & 3));
    o32[0] = hadd2_bf(hmul2_bf(gA, ax), hmul2_bf(hsub2_bf(one2, gA), hfma2_bf(pack_bf16(sx0, sx1), half2, bb)));
    o32[4 * D_MODEL] = hadd2_bf(hmul2_bf(gB, ay), hmul2_bf(hsub2_bf(one2, gB), hfma2_bf(pack_bf16(sy0, sy1), half2, bb)));
}
constexpr int NFIN_HELP = 5;

template <int EPI>
__device__ __forceinline__ void run_chunk(float (&cur)[32], float (&prev)[32], const uint32_t (&af)[NAF][4],
                                          int parity, uint32_t bars, uint32_t desc0, uint32_t adesc0, uint32_t p0, uint32_t p1,
                                          uint4* part, bool sig, uint32_t rbar, int lane, float r0, float r1) {
#pragma unroll
    for (int s = 0; s < 6; s++) {
        mbar_wait(bars + BAR_FULL + s * 8, parity);
        WG_FENCE();
        mma_stage_rt(s, cur, af, desc0, adesc0);
        WG_COMMIT();
        if (s >= 1 && s <= 4) {
            if (EPI == 1) epi_park(prev, s - 1, p0, p1, r0, r1);
            if (EPI == 2) epi_part(prev, s - 1, part, p1);
        }
        if (s == 4 && EPI == 2) warp_arrive(p0, lane);
        WG_WAIT(1);
        if (sig) asm volatile("mbarrier.arrive.shared::cluster.b64 _, [%0];" ::"r"(rbar + ((s + 5) % 6) * 8) : "memory");
        if (s == 0) fence_acc(prev);
    }
}

__global__ void __cluster_dims__(2, 1, 1) __launch_bounds__(384, 1)
mlp_kernel(const __grid_constant__ CUtensorMap tmx, const __grid_constant__ CUtensorMap tmw1,
           const __grid_constant__ CUtensorMap tmw2, const __grid_constant__ CUtensorMap tma,
           const bf16* __restrict__ b1, const bf16* __restrict__ b2,
           bf16* __restrict__ out) {
    extern __shared__ __align__(1024) uint8_t smem_raw[];
    const uint32_t sbase = smem_u32(smem_raw);
    uint8_t* sgen = smem_raw;
    const int tid = threadIdx.x, lane = tid & 31;
    const int warp = __shfl_sync(0xffffffffu, tid >> 5, 0);
    const int wgid = __shfl_sync(0xffffffffu, tid >> 7, 0);
    const int m = blockIdx.x & 15, f = blockIdx.x >> 4;
    const uint32_t rank = m & 1;
    const uint32_t bars = sbase + SM_BARS;
    if (warp == 0) DBG(12);

    if (tid == 0) {
        if (sbase & 1023) asm volatile("trap; // 2");
        for (int i = 0; i < NSTAGE; i++) {
            mbar_init(bars + BAR_FULL + i * 8, 1);
            mbar_init(bars + BAR_EMPTY + i * 8, 4);
        }
        for (int i = 0; i < 9; i++) mbar_init(bars + BAR_X + i * 8, 1);
        mbar_init(bars + BAR_PARKFREE, 8);
        mbar_init(bars + BAR_A, 1);
        for (int i = 0; i < 9; i++) {
            mbar_init(bars + BAR_STORED + i * 8, 8);
            mbar_init(bars + BAR_LOADED + i * 8, 1);
        }
        asm volatile("fence.mbarrier_init.release.cluster;" ::: "memory");
        for (int j = 0; j < 3; j++) {
            mbar_expect(bars + BAR_X + j * 8, 16384);
            tma2d(sbase + j * 16384, &tmx, j * 64, m * 128, bars + BAR_X + j * 8);
        }
    }
    uint32_t b1v0 = 0, b1v1 = 0;
    if (wgid < 2) {
        const uint32_t* b1w = reinterpret_cast<const uint32_t*>(b1 + f * 576);
        b1v0 = __ldg(b1w + (tid >> 5) * 32 + (tid & 7) * 4 + ((tid >> 3) & 3));
        if (tid < 32) b1v1 = __ldg(b1w + 8 * 32 + (tid & 7) * 4 + ((tid >> 3) & 3));
    }
    __syncthreads();
    asm volatile("barrier.cluster.arrive.relaxed.aligned;\nbarrier.cluster.wait.aligned;" ::: "memory");

    if (warp == 0) DBG(0);
    if (wgid == 2) {
        asm volatile("setmaxnreg.dec.sync.aligned.u32 40;");
        if (warp == 8) {
            if (lane == 0) {
                const uint32_t dst0 = sbase + SM_STAGES + rank * (STAGE_BYTES / 2);
#pragma unroll 1
                for (int cc = 0; cc < 18; cc++) {
                    const CUtensorMap* tm = cc < 9 ? &tmw1 : &tmw2;
                    const int c0 = cc < 9 ? f * 576 + cc * 64 : (cc - 9) * 64;
                    const int c1 = (cc < 9 ? 0 : f * 576) + rank * 48;
                    const int par = (cc & 1) ^ 1;
#pragma unroll
                    for (int s = 0; s < 6; s++) {
                        mbar_wait(bars + BAR_EMPTY + s * 8, par);
                        mbar_expect(bars + BAR_FULL + s * 8, STAGE_BYTES);
                        tma2d_mc(dst0 + s * STAGE_BYTES, tm, c0, c1 + s * 96, bars + BAR_FULL + s * 8, 3);
                        if (cc == 0 && s >= 1 && s <= 3) {
#pragma unroll
                            for (int j = 2 * s + 1; j < 2 * s + 3; j++) {
                                mbar_expect(bars + BAR_X + j * 8, 16384);
                                tma2d(sbase + j * 16384, &tmx, j * 64, m * 128, bars + BAR_X + j * 8);
                            }
                        }
                    }
                }
            }
        } else if (warp == 9) {
            {
                uint32_t* b2s = reinterpret_cast<uint32_t*>(sgen + SM_B2);
                for (int w = lane; w < 288; w += 32) {
                    const int jj = w & 1, q = (w >> 1) & 3, ci = w >> 3;
                    b2s[w] = __ldg(reinterpret_cast<const uint32_t*>(b2) + ci * 8 + jj * 4 + q);
                }
                __syncwarp();
            }
            asm volatile("griddepcontrol.wait;" ::: "memory");
            const uint32_t par = __ldcg(&g_epoch);
            mbar_wait(bars + BAR_PARKFREE, 0);
            asm volatile("fence.proxy.async.shared::cta;" ::: "memory");
            const uint4* psrc = g_part + (m * 9 * 8 + f) * (8 * 4 * 32);
#pragma unroll 1
            for (int c = 0; c < 8; c++) {
                const uint32_t buf = sbase + red_buf(c);
                if (c == 7) {
                    mbar_wait(bars + BAR_STORED + 7 * 8, 0);
                    mbar_wait(bars + BAR_EMPTY + 0, 1);
                    mbar_wait(bars + BAR_EMPTY + 8, 1);
                    mbar_wait(bars + BAR_EMPTY + 16, 1);
                }
                if (lane == 0) {
                    mbar_expect(bars + BAR_LOADED + c * 8, c < 8 ? 16384 + 2048 : 2048);
                    tma2d(buf + 16384, &tma, m * 128 + f * 16, c * 64, bars + BAR_LOADED + c * 8);
                    if (c == 7) {
                        mbar_expect(bars + BAR_LOADED + 64, 2048);
                        tma2d(sbase + red_buf(8) + 16384, &tma, m * 128 + f * 16, 8 * 64, bars + BAR_LOADED + 64);
                    }
                }
                mbar_wait(bars + BAR_STORED + c * 8, 0);
                probe_partials(psrc + (lane & 7) * 128 + 96 + 31, par);
                DBG(16 + c);
                if (lane == 0)
                    asm volatile("cp.async.bulk.shared::cluster.global.mbarrier::complete_tx::bytes [%0], [%1], 16384, [%2];"
                                 ::"r"(buf), "l"(psrc), "r"(bars + BAR_LOADED + c * 8) : "memory");
                psrc += 8 * 8 * 4 * 32;
            }
        }
        if (warp >= 10) {
            mbar_wait(bars + BAR_PARKFREE, 0);
            asm volatile("griddepcontrol.wait;" ::: "memory");
            const int t0 = m * 128 + f * 16 + (lane >> 2);
            const float g0 = __ldcg(&g_gate[t0]), g1 = __ldcg(&g_gate[t0 + 8]);
            const uint32_t par = __ldcg(&g_epoch) & 1u;
            const uint32_t gA = pack_bf16(g0, g0), gB = pack_bf16(g1, g1);
#pragma unroll 1
            for (int it = 0; it < NFIN_HELP * 4; it++) {
                if (!(it & 3)) mbar_wait(bars + BAR_LOADED + (it >> 2) * 8, 0);
                finish_tile(it >> 2, (it & 3) * 2 + (warp & 1), sbase, par, gA, gB, out);
            }
        }
        __syncwarp();
        asm volatile("barrier.cluster.arrive.relaxed.aligned;\nbarrier.cluster.wait.aligned;" ::: "memory");
    } else {
        asm volatile("setmaxnreg.inc.sync.aligned.u32 232;");
        const uint32_t par = __ldcg(&g_epoch) & 1u;
        uint2 rs0, rs1;
        {
            const uint2* rp = &g_rowstat[m * 128 + warp * 16 + (lane >> 2)];
            int tries = 0;
            while (true) {
                unsigned long long e0, e1;
                asm volatile("ld.relaxed.gpu.global.b64 %0, [%1];" : "=l"(e0) : "l"(rp) : "memory");
                asm volatile("ld.relaxed.gpu.global.b64 %0, [%1];" : "=l"(e1) : "l"(rp + 8) : "memory");
                rs0 = make_uint2((uint32_t)e0, (uint32_t)(e0 >> 32));
                rs1 = make_uint2((uint32_t)e1, (uint32_t)(e1 >> 32));
                if (!__any_sync(0xffffffffu, ((rs0.y ^ par) | (rs1.y ^ par)) & 1)) break;
                if (++tries > (1 << 22)) asm volatile("trap; // 3");
            }
        }
        const int g = lane >> 2, tq = lane & 3;
        uint32_t af[NAF][4];
        float acc0[32], acc1[32];
        const bool sig = (tid & 127) < 2;
        uint32_t rbar;
        asm volatile("mapa.shared::cluster.u32 %0, %1, %2;" : "=r"(rbar) : "r"(bars + BAR_EMPTY), "r"(tid & 1));
        const uint32_t desc0 = ((sbase + SM_STAGES) & 0x3FFFF) >> 4;
        const uint32_t adesc0 = ((sbase + 8 * 16384 + wgid * 8192) & 0x3FFFF) >> 4;

        {
            float2* b1s = reinterpret_cast<float2*>(sgen + SM_B1);
            b1s[tid] = make_float2(bf_lo(b1v0), bf_hi(b1v0));
            if (tid < 32) b1s[256 + tid] = make_float2(bf_lo(b1v1), bf_hi(b1v1));
        }
        const float rstd0 = __uint_as_float(rs0.y), rstd1 = __uint_as_float(rs1.y);
        {
            const int lrow = warp * 16 + (lane & 7) + ((lane >> 3) & 1) * 8;
            const uint32_t rbase = sbase + lrow * 128;
            const int hi = lane >> 4, sw = lrow & 7;
#pragma unroll
            for (int s = 0; s < 6; s++) {
#pragma unroll
                for (int k = s * 6; k < s * 6 + 6; k++) {
                    const int j = k >> 2, kk = k & 3;
                    if (kk == 0 || k == s * 6) mbar_wait(bars + BAR_X + j * 8, 0);
                    uint32_t tmp[4];
                    uint32_t (&a)[4] = (k < NAF) ? af[(k < NAF) ? k : 0] : tmp;
                    const uint32_t addr = rbase + j * 16384 + (((kk * 2 + hi) ^ sw) << 4);
                    ldsm_x4(a, addr);
                    a[0] = hsub2_bf(a[0], rs0.x);
                    a[1] = hsub2_bf(a[1], rs1.x);
                    a[2] = hsub2_bf(a[2], rs0.x);
                    a[3] = hsub2_bf(a[3], rs1.x);
                    if (k >= NAF) stsm_x4(a, addr);
                }
                if (s == 5) {
                    asm volatile("fence.proxy.async.shared::cta;" ::: "memory");
                    asm volatile("bar.sync %0, 128;" ::"r"(3 + wgid) : "memory");
                    if (warp == 0) DBG(1);
                }
                mbar_wait(bars + BAR_FULL + s * 8, 0);
                WG_FENCE();
                mma_stage_rt(s, acc0, af, desc0, adesc0);
                WG_COMMIT();
                if (s > 0) {
                    WG_WAIT(1);
                    if (sig) asm volatile("mbarrier.arrive.shared::cluster.b64 _, [%0];" ::"r"(rbar + (s - 1) * 8) : "memory");
                }
            }
            asm volatile("bar.sync 1, 256;" ::: "memory");
        }
        {
            uint32_t b1a = sbase + SM_B1 + tq * 64, park = sbase + tid * 16;
#pragma unroll 1
            for (int c = 1; c < 9; c += 2) {
                if (warp == 0) DBG(2 + (c >> 1));
                run_chunk<1>(acc1, acc0, af, 1, bars, desc0, adesc0, b1a, park, nullptr, sig, rbar, lane, rstd0, rstd1);
                run_chunk<1>(acc0, acc1, af, 0, bars, desc0, adesc0, b1a + 256, park + 16384, nullptr, sig, rbar, lane, rstd0, rstd1);
                b1a += 512;
                park += 32768;
            }
        }
        if (warp == 0) DBG(6);
        WG_WAIT(0);
        if (sig) asm volatile("mbarrier.arrive.shared::cluster.b64 _, [%0];" ::"r"(rbar + 5 * 8) : "memory");
        fence_acc(acc0);
        {
#pragma unroll
            for (int s = 0; s < 6; s++) {
#pragma unroll
                for (int k = (s == 0 ? 0 : s * 6 + 6); k < s * 6 + 12 && k < 32; k++)
                    asm volatile("ld.shared.v4.b32 {%0,%1,%2,%3}, [%4];"
                                 : "=r"(af[k][0]), "=r"(af[k][1]), "=r"(af[k][2]), "=r"(af[k][3])
                                 : "r"(sbase + tid * 16 + k * 4096) : "memory");
                mbar_wait(bars + BAR_FULL + s * 8, 1);
                WG_FENCE();
                mma_stage_rt(s, acc1, af, desc0, adesc0);
                WG_COMMIT();
                if (s < 2) epi_gelu(acc0, s, sbase + SM_B1 + tq * 64 + 8 * 256, rstd0, rstd1, af[32 + (s & 1)]);
                if (s == 2 || s == 3) {
                    uint32_t tmp[4];
                    epi_gelu(acc0, s, sbase + SM_B1 + tq * 64 + 8 * 256, rstd0, rstd1, tmp);
                    const int lrow = warp * 16 + (lane & 7) + ((lane >> 3) & 1) * 8;
                    stsm_x4(tmp, sbase + 8 * 16384 + lrow * 128 + (((s * 2 + (lane >> 4)) ^ (lrow & 7)) << 4));
                }
                if (s == 3) {
                    asm volatile("fence.proxy.async.shared::cta;" ::: "memory");
                    asm volatile("bar.sync %0, 128;" ::"r"(3 + wgid) : "memory");
                }
                if (s > 0) {
                    WG_WAIT(1);
                    if (sig) asm volatile("mbarrier.arrive.shared::cluster.b64 _, [%0];" ::"r"(rbar + (s - 1) * 8) : "memory");
                }
                if (s == 5) warp_arrive(bars + BAR_PARKFREE, lane);
            }
        }
        uint4* part = g_part + (size_t)((m * 9 * 8 + warp) * 8 + f) * (4 * 32) + lane;
        uint32_t stored = bars + BAR_STORED;
#pragma unroll 1
        for (int c = 1; c < 9; c += 2) {
            if (warp == 0) DBG(7 + (c >> 1));
            run_chunk<2>(acc0, acc1, af, 0, bars, desc0, adesc0, stored, par, part, sig, rbar, lane, 0.f, 0.f);
            run_chunk<2>(acc1, acc0, af, 1, bars, desc0, adesc0, stored + 8, par, part + 8 * 8 * 4 * 32, sig, rbar, lane, 0.f, 0.f);
            part += 2 * 8 * 8 * 4 * 32;
            stored += 16;
        }
        const int t0 = m * 128 + f * 16 + g;
        asm volatile("griddepcontrol.wait;" ::: "memory");
        const float g0 = __ldcg(&g_gate[t0]), g1 = __ldcg(&g_gate[t0 + 8]);
        WG_WAIT(0);
        fence_acc(acc1);
#pragma unroll
        for (int i = 0; i < 4; i++) epi_part(acc1, i, part, par);
        asm volatile("barrier.cluster.arrive.relaxed.aligned;" ::: "memory");
        if (warp == 0) DBG(11);
        {
            const uint32_t gA = pack_bf16(g0, g0), gB = pack_bf16(g1, g1);
            const uint32_t half2 = 0x3f003f00u, one2 = 0x3f803f80u;
            const uint32_t oA = hsub2_bf(one2, gA), oB = hsub2_bf(one2, gB);
            uint32_t* o32 = reinterpret_cast<uint32_t*>(out + (size_t)t0 * D_MODEL + 2 * tq) + warp * 4;
            const uint32_t lm = sbase + 16384 + (lane & 7) * 32 + ((lane >> 3) & 1) * 16 + warp * 256;
            const uint32_t a0 = sbase + (warp >> 1) * 512 + lane * 16 + (warp & 1) * 8;
            const uint32_t b2a = sbase + SM_B2 + (warp >> 1) * 32 + tq * 8 + (warp & 1) * 4;
            const uint2* ps0 = reinterpret_cast<const uint2*>(
                g_part + (m * 9 * 8 + f) * (8 * 4 * 32) + (warp >> 1) * 32 + lane) + (warp & 1);
            uint2 v[4][8], av[4];
            uint32_t bb[4], bad = 0;
#pragma unroll
            for (int k = 0; k < 4; k++) {
                const int c = NFIN_HELP + k;
                const uint32_t bo = red_buf(c);
                mbar_wait(bars + BAR_LOADED + c * 8, 0);
                if (k < 3) {
#pragma unroll
                    for (int q = 0; q < 8; q++) {
                        v[k][q] = ssm::lds64(a0 + bo + q * 2048);
                        bad |= v[k][q].x ^ par;
                    }
                }
                asm volatile("ldmatrix.sync.aligned.m8n8.x2.trans.shared.b16 {%0,%1}, [%2];"
                             : "=r"(av[k].x), "=r"(av[k].y) : "r"(lm + bo) : "memory");
                bb[k] = ssm::lds32(b2a + c * 128);
            }
            auto emit = [&](int k) {
                const int c = NFIN_HELP + k;
                float sx0 = 0.f, sx1 = 0.f, sy0 = 0.f, sy1 = 0.f;
#pragma unroll
                for (int q = 0; q < 8; q++) {
                    sx0 += bf_lo(v[k][q].x); sx1 += bf_hi(v[k][q].x);
                    sy0 += bf_lo(v[k][q].y); sy1 += bf_hi(v[k][q].y);
                }
                o32[c * 32] = hadd2_bf(hmul2_bf(gA, av[k].x), hmul2_bf(oA, hfma2_bf(pack_bf16(sx0, sx1), half2, bb[k])));
                o32[c * 32 + 4 * D_MODEL] =
                    hadd2_bf(hmul2_bf(gB, av[k].y), hmul2_bf(oB, hfma2_bf(pack_bf16(sy0, sy1), half2, bb[k])));
            };
            auto reload = [&](int k) {
                uint32_t b = 0;
#pragma unroll
                for (int q = 0; q < 8; q++) {
                    unsigned long long w;
                    asm volatile("ld.relaxed.gpu.global.b64 %0, [%1];" : "=l"(w)
                                 : "l"(ps0 + (NFIN_HELP + k) * (8 * 8 * 4 * 32 * 2) + q * 256) : "memory");
                    v[k][q] = make_uint2((uint32_t)w, (uint32_t)(w >> 32));
                    b |= v[k][q].x ^ par;
                }
                return b;
            };
            int tries = 0;
            while (__any_sync(0xffffffffu, bad & 1)) {
                bad = reload(0) | reload(1) | reload(2);
                if (++tries > (1 << 20)) break;
            }
            emit(0); emit(1); emit(2);
            if (warp == 0) DBG(32);
            probe_partials(g_part + ((m * 9 + 8) * 8 + f) * (8 * 4 * 32) + (lane & 7) * 128 + (warp >> 1) * 32 + 31, par);
            do {
                bad = reload(3);
                if (++tries > (1 << 20)) break;
            } while (__any_sync(0xffffffffu, bad & 1));
            emit(3);
            if (warp == 0) DBG(33);
        }
        asm volatile("barrier.cluster.wait.aligned;" ::: "memory");
        if (warp == 0) DBG(13);
    }
}

typedef CUresult (*EncodeFn)(CUtensorMap*, CUtensorMapDataType, cuuint32_t, void*, const cuuint64_t*,
                             const cuuint64_t*, const cuuint32_t*, const cuuint32_t*, CUtensorMapInterleave,
                             CUtensorMapSwizzle, CUtensorMapL2promotion, CUtensorMapFloatOOBfill);

static void make_map(EncodeFn enc, CUtensorMap* m, const void* ptr, uint64_t cols, uint64_t rows, uint32_t box_c,
                     uint32_t box_r, CUtensorMapSwizzle swz = CU_TENSOR_MAP_SWIZZLE_128B) {
    cuuint64_t dim[2] = {cols, rows};
    cuuint64_t str[1] = {cols * 2};
    cuuint32_t box[2] = {box_c, box_r};
    cuuint32_t es[2] = {1, 1};
    enc(m, CU_TENSOR_MAP_DATA_TYPE_BFLOAT16, 2, const_cast<void*>(ptr), dim, str, box, es,
        CU_TENSOR_MAP_INTERLEAVE_NONE, swz, CU_TENSOR_MAP_L2_PROMOTION_L2_128B,
        CU_TENSOR_MAP_FLOAT_OOB_FILL_NONE);
}

}

extern "C" void kernel_launch(void* const* d_in, const int* in_sizes, int n_in, void* d_out, int out_size) {
    const bf16* u = (const bf16*)d_in[0];
    const bf16* A_re = (const bf16*)d_in[1];
    const bf16* A_im = (const bf16*)d_in[2];
    const bf16* B_re = (const bf16*)d_in[3];
    const bf16* B_im = (const bf16*)d_in[4];
    const bf16* C_re = (const bf16*)d_in[5];
    const bf16* C_im = (const bf16*)d_in[6];
    const bf16* log_dt = (const bf16*)d_in[7];
    const bf16* Dskip = (const bf16*)d_in[8];
    const bf16* w1 = (const bf16*)d_in[10];
    const bf16* b1 = (const bf16*)d_in[11];
    const bf16* w2 = (const bf16*)d_in[12];
    const bf16* b2 = (const bf16*)d_in[13];
    const bf16* gw = (const bf16*)d_in[14];
    bf16* out = (bf16*)d_out;

    static EncodeFn enc = nullptr;
    if (!enc) {
        void* fn = nullptr;
        cudaDriverEntryPointQueryResult q;
        cudaGetDriverEntryPoint("cuTensorMapEncodeTiled", &fn, cudaEnableDefault, &q);
        enc = (EncodeFn)fn;
        cudaFuncSetAttribute(mlp_kernel, cudaFuncAttributeMaxDynamicSharedMemorySize, MLP_SMEM);
        cudaFuncSetAttribute(ssm::ssm_kernel, cudaFuncAttributeMaxDynamicSharedMemorySize, ssm::K1_SMEM);
    }
    static void* aT_ptr = nullptr;
    if (!aT_ptr) cudaGetSymbolAddress(&aT_ptr, g_aT);
    CUtensorMap tmx, tmw1, tmw2, tma;
    make_map(enc, &tma, aT_ptr, L_SEQ, D_MODEL, 16, 64, CU_TENSOR_MAP_SWIZZLE_NONE);
    make_map(enc, &tmx, u, D_MODEL, L_SEQ, 64, 128);
    make_map(enc, &tmw1, w1, F_DIM, D_MODEL, 64, 48);
    make_map(enc, &tmw2, w2, D_MODEL, F_DIM, 64, 48);

    cudaStream_t st = cudaStreamPerThread;
    ssm::Params sp{A_re, A_im, B_re, B_im, C_re, C_im, log_dt, Dskip};
    CUtensorMap tmc, tmo;
    make_map(enc, &tmc, u, D_MODEL, L_SEQ, 8, 256, CU_TENSOR_MAP_SWIZZLE_NONE);
    make_map(enc, &tmo, aT_ptr, 64, D_MODEL * 32, 64, 32);
    ssm::ssm_kernel<<<ssm::K1_CTAS + ssm::K1_STAT, 128 * ssm::K1_WGS, ssm::K1_SMEM, st>>>(tmc, tmo, u, gw, sp);
    cudaLaunchConfig_t cfg = {};
    cfg.gridDim = dim3(128);
    cfg.blockDim = dim3(384);
    cfg.dynamicSmemBytes = MLP_SMEM;
    cfg.stream = st;
    cudaLaunchAttribute at[1];
    at[0].id = cudaLaunchAttributeProgrammaticStreamSerialization;
    at[0].val.programmaticStreamSerializationAllowed = 1;
    cfg.attrs = at;
    cfg.numAttrs = 1;
    cudaLaunchKernelEx(&cfg, mlp_kernel, tmx, tmw1, tmw2, tma, b1, b2, out);
}
```
